```python
import torch

def _softmax(x, axis=-1):
    return torch.softmax(x, dim=axis)
def _gelu(x):
    return torch.nn.functional.gelu(x, approximate="tanh")
def _silu(x):
    return torch.nn.functional.silu(x)
def _sigmoid(x):
    return torch.sigmoid(x)
def _layernorm(x, axis=-1, eps=1e-5):
    m = x.mean(dim=axis, keepdim=True)
    v = x.var(dim=axis, keepdim=True, unbiased=False)
    return (x - m) / torch.sqrt(v + eps)
def _scatter_add(tgt, idx, src, axis=0):
    return tgt.clone().index_add_(axis, idx, src)
def _segment_sum(src, seg, n):
    out = torch.zeros((n,) + src.shape[1:], dtype=src.dtype)
    return out.index_add_(0, seg, src)
def _pad(x, pw):
    flat = tuple(v for pair in reversed(pw) for v in pair)
    return torch.nn.functional.pad(x, flat)

kernel_name = 'parallel_sum__sliding_local_dilated__glu_gated_swiglu__prompt'

def setup_inputs():

    _w = (lambda a: (lambda t: t.to(torch.bfloat16) if t.is_floating_point() else t)(torch.as_tensor(a)))
    def _A_setup():
        B, S, D = 1, 2048, 640
        return {
            "x": _w((lambda *s: torch.randn(*s, dtype=torch.bfloat16) * 0.05)(B, S, D)),
            "wqkv": _w((lambda *s: torch.randn(*s, dtype=torch.bfloat16) * 0.05)(D, 3 * D)),
            "wo": _w((lambda *s: torch.randn(*s, dtype=torch.bfloat16) * 0.05)(D, D)),
        }
    _A_in = _A_setup()

    def _B_setup():
        B, S, D, F = 1, 2048, 640, 1536
        return {
            "x": _w((lambda *s: torch.randn(*s, dtype=torch.bfloat16) * 0.05)(B, S, D)),
            "w1": _w((lambda *s: torch.randn(*s, dtype=torch.bfloat16) * 0.8)(D, F) * (2.0 / D) ** 0.5),
            "w3": _w((lambda *s: torch.randn(*s, dtype=torch.bfloat16) * 0.8)(D, F) * (2.0 / D) ** 0.5),
            "w2": _w((lambda *s: torch.randn(*s, dtype=torch.bfloat16) * 0.8)(F, D) * (2.0 / F) ** 0.5),
        }
    _B_in = _B_setup()

    return {
        "A_x": _A_in["x"],
        "A_wqkv": _A_in["wqkv"],
        "A_wo": _A_in["wo"],
        "B_x": _B_in["x"],
        "B_w1": _B_in["w1"],
        "B_w3": _B_in["w3"],
        "B_w2": _B_in["w2"],
    }

def reference(A_x, A_wqkv, A_wo, B_x, B_w1, B_w3, B_w2):
    def _A_ref(x, wqkv, wo):
        B, S, D = x.shape
        H = 32; Dh = D // H
        W, dil = 8, 2
        qkv = (lambda x, *d: x.permute(*d))((x @ wqkv).reshape(B, S, 3, H, Dh), 2, 0, 3, 1, 4)
        q, k, v = qkv[0], qkv[1], qkv[2]
        scale = Dh ** -0.5
        pos = torch.arange(S)
        off = torch.arange(W) * dil
        idx = pos[:, None] - off[None, :]
        mask = idx >= 0
        idx_c = torch.where(mask, idx, 0).reshape(-1)
        kg = k[:, :, idx_c, :].reshape(B, H, S, W, Dh)
        vg = v[:, :, idx_c, :].reshape(B, H, S, W, Dh)
        logits = torch.einsum("bhsd,bhswd->bhsw", q, kg) * scale
        logits = torch.where(mask[None, None, :, :], logits, -1e9)
        attn = _softmax(logits, axis=-1)
        o = torch.einsum("bhsw,bhswd->bhsd", attn, vg)
        return (lambda x, *d: x.permute(*d))(o, 0, 2, 1, 3).reshape(B, S, D) @ wo

    def _B_ref(x, w1, w3, w2):
        gate = torch.einsum("bsd,df->bsf", x, w1)
        up = torch.einsum("bsd,df->bsf", x, w3)
        h = _silu(gate) * up
        out = torch.einsum("bsf,fd->bsd", h, w2)
        return out

    x = A_x
    xn = _layernorm(x, axis=-1)
    return x + _A_ref(xn, A_wqkv, A_wo) + _B_ref(xn, B_w1, B_w3, B_w2)
```

```cpp
#include <cuda_runtime.h>
#include <cuda_bf16.h>
#include <cuda.h>
#include <stdint.h>

namespace {

constexpr int S_ = 2048, D_ = 640, F_ = 1536, NQKV = 1920;
constexpr int NTHREADS = 384;

constexpr int SM_X    = 0;
constexpr int SM_RING = 163840;
constexpr int SLOT    = 16384;
constexpr int CSLOT   = 34816;
constexpr int SM_CS   = 229376;
constexpr int SM_BAR  = 231872;
constexpr int SM_TOTAL = 232448;
constexpr int B_XFULL = 0, B_FULL = 10, B_EMPTY = 14, B_CFULL = 18, B_CEMPTY = 24, B_EPI = 28, B_GU = 29,
              B_QKVDONE = 30, B_QKVRDY = 31, B_RFULL = 32, B_REMPTY = 42;
constexpr int SM_RECV = 208896;

constexpr uint32_t SPIN_LIMIT = 1u << 17;
constexpr uint32_t DESC_HI = 0x40000040u;

constexpr int BLK = 8192;
__device__ uint2  g_qkv[120 * BLK];
__device__ uint4  g_part[16 * 10 * 2 * 4 * 4 * 128];
__device__ float2 g_stats[S_];
__device__ float4 g_cs[8 * 16 * 160];
constexpr int FL_DONE = 0, FL_QKV = 1, FL_COUNT = 17;
__device__ unsigned g_flags[FL_COUNT * 32];
#define TSTAMP(id) do {} while (0)
#define GSTAMP(id) do {} while (0)

struct Params {
  const __nv_bfloat16* x;
  const __nv_bfloat16* wqkv;
  const __nv_bfloat16* w1;
  const __nv_bfloat16* w3;
  const __nv_bfloat16* w2;
  const __nv_bfloat16* wo;
  __nv_bfloat16* out;
};

__device__ __forceinline__ uint32_t smem_u32(const void* p) { return (uint32_t)__cvta_generic_to_shared(p); }
__device__ __forceinline__ void mbar_init(uint32_t bar, uint32_t cnt) {
  asm volatile("mbarrier.init.shared::cta.b64 [%0], %1;" ::"r"(bar), "r"(cnt) : "memory");
}
__device__ __forceinline__ void mbar_expect_tx(uint32_t bar, uint32_t bytes) {
  asm volatile("mbarrier.arrive.expect_tx.shared::cta.b64 _, [%0], %1;" ::"r"(bar), "r"(bytes) : "memory");
}
__device__ __forceinline__ void mbar_arrive(uint32_t bar) {
  asm volatile("mbarrier.arrive.shared::cta.b64 _, [%0];" ::"r"(bar) : "memory");
}
__device__ __forceinline__ bool mbar_try(uint32_t bar, uint32_t parity) {
  uint32_t ok;
  asm volatile("{\n.reg .pred p;\nmbarrier.try_wait.parity.shared::cta.b64 p, [%1], %2;\nselp.u32 %0, 1, 0, p;\n}"
               : "=r"(ok) : "r"(bar), "r"(parity) : "memory");
  return ok != 0;
}
__device__ __forceinline__ void mbar_wait(uint32_t bar, uint32_t parity) {
  uint32_t it = 0;
#pragma unroll 1
  while (!mbar_try(bar, parity)) { if (++it > SPIN_LIMIT) break; }
}
__device__ __forceinline__ void tma2d(uint32_t dst, const CUtensorMap* m, int c0, int c1, uint32_t bar) {
  asm volatile("cp.async.bulk.tensor.2d.shared::cluster.global.mbarrier::complete_tx::bytes [%0], [%1, {%3, %4}], [%2];"
               ::"r"(dst), "l"(m), "r"(bar), "r"(c0), "r"(c1) : "memory");
}
__device__ __forceinline__ void tma3d(uint32_t dst, const CUtensorMap* m, int c0, int c1, int c2, uint32_t bar) {
  asm volatile("cp.async.bulk.tensor.3d.shared::cluster.global.mbarrier::complete_tx::bytes [%0], [%1, {%3, %4, %5}], [%2];"
               ::"r"(dst), "l"(m), "r"(bar), "r"(c0), "r"(c1), "r"(c2) : "memory");
}
__device__ __forceinline__ void prefetch_tmap(const CUtensorMap* m) {
  asm volatile("prefetch.tensormap [%0];" ::"l"(m) : "memory");
}
__device__ __forceinline__ void wg_fence() { asm volatile("wgmma.fence.sync.aligned;" ::: "memory"); }
__device__ __forceinline__ void wg_commit() { asm volatile("wgmma.commit_group.sync.aligned;" ::: "memory"); }
template <int N> __device__ __forceinline__ void wg_wait() { asm volatile("wgmma.wait_group.sync.aligned %0;" ::"n"(N) : "memory"); }
template <int N> __device__ __forceinline__ void fence_regs(float (&a)[N]) {
#pragma unroll
  for (int i = 0; i < N; i++) asm volatile("" : "+f"(a[i]) :: "memory");
}
__device__ __forceinline__ uint32_t pack_bf16(float lo, float hi) {
  uint32_t r;
  asm("cvt.rn.bf16x2.f32 %0, %1, %2;" : "=r"(r) : "f"(hi), "f"(lo));
  return r;
}
__device__ __forceinline__ float bf_lo(uint32_t w) { return __uint_as_float(w << 16); }
__device__ __forceinline__ float bf_hi(uint32_t w) { return __uint_as_float(w & 0xffff0000u); }
__device__ __forceinline__ float2 lds64f(uint32_t addr) {
  float2 v;
  asm volatile("ld.shared.v2.f32 {%0, %1}, [%2];" : "=f"(v.x), "=f"(v.y) : "r"(addr));
  return v;
}
__device__ __forceinline__ void sts128f(uint32_t addr, float4 v) {
  asm volatile("st.shared.v4.f32 [%0], {%1, %2, %3, %4};" ::"r"(addr), "f"(v.x), "f"(v.y), "f"(v.z), "f"(v.w) : "memory");
}
__device__ __forceinline__ void flag_signal(unsigned* f) {
  asm volatile("red.release.gpu.global.add.u32 [%0], 1;" ::"l"(f) : "memory");
}
__device__ __forceinline__ void flag_wait(const unsigned* f, unsigned target) {
  uint32_t it = 0;
  while (true) {
    unsigned v;
    asm volatile("ld.acquire.gpu.global.u32 %0, [%1];" : "=r"(v) : "l"(f) : "memory");
    if ((int)(v - target) >= 0) break;
    if (++it > SPIN_LIMIT) break;
  }
}
__device__ __forceinline__ float ex2f(float x) { float y; asm("ex2.approx.ftz.f32 %0, %1;" : "=f"(y) : "f"(x)); return y; }
__device__ __forceinline__ float rcpf(float x) { float y; asm("rcp.approx.ftz.f32 %0, %1;" : "=f"(y) : "f"(x)); return y; }
__device__ __forceinline__ void mma16816(float (&c)[4], uint32_t a0, uint32_t a1, uint32_t a2, uint32_t a3, uint32_t b0, uint32_t b1) {
  asm volatile("mma.sync.aligned.m16n8k16.row.col.f32.bf16.bf16.f32 {%0,%1,%2,%3}, {%4,%5,%6,%7}, {%8,%9}, {%0,%1,%2,%3};"
               : "+f"(c[0]), "+f"(c[1]), "+f"(c[2]), "+f"(c[3]) : "r"(a0), "r"(a1), "r"(a2), "r"(a3), "r"(b0), "r"(b1));
}
__device__ __forceinline__ void mma1688(float (&c)[4], uint32_t a0, uint32_t a1, uint32_t b0) {
  asm volatile("mma.sync.aligned.m16n8k8.row.col.f32.bf16.bf16.f32 {%0,%1,%2,%3}, {%4,%5}, {%6}, {%0,%1,%2,%3};"
               : "+f"(c[0]), "+f"(c[1]), "+f"(c[2]), "+f"(c[3]) : "r"(a0), "r"(a1), "r"(b0));
}
__device__ __forceinline__ uint32_t movm(uint32_t a) {
  uint32_t d;
  asm volatile("movmatrix.sync.aligned.m8n8.trans.b16 %0, %1;" : "=r"(d) : "r"(a));
  return d;
}

__device__ __forceinline__ uint32_t mapa(uint32_t addr, uint32_t rank) {
  uint32_t r;
  asm("mapa.shared::cluster.u32 %0, %1, %2;" : "=r"(r) : "r"(addr), "r"(rank));
  return r;
}
__device__ __forceinline__ void mbar_arrive_remote(uint32_t cluster_addr) {
  asm volatile("mbarrier.arrive.shared::cluster.b64 _, [%0];" ::"r"(cluster_addr) : "memory");
}
__device__ __forceinline__ void st_async(uint32_t cluster_addr, uint4 v, uint32_t cluster_bar) {
  asm volatile("st.async.weak.shared::cluster.mbarrier::complete_tx::bytes.v4.b32 [%0], {%1, %2, %3, %4}, [%5];"
               ::"r"(cluster_addr), "r"(v.x), "r"(v.y), "r"(v.z), "r"(v.w), "r"(cluster_bar) : "memory");
}
__device__ __forceinline__ uint4 lds128(uint32_t addr) {
  uint4 v;
  asm volatile("ld.shared.v4.b32 {%0, %1, %2, %3}, [%4];" : "=r"(v.x), "=r"(v.y), "=r"(v.z), "=r"(v.w) : "r"(addr) : "memory");
  return v;
}
__device__ __forceinline__ void st_tagged(void* p, uint4 v) {
  asm volatile("{\n.reg .b128 r;\nmov.b128 r, {%1, %2};\nst.relaxed.gpu.global.b128 [%0], r;\n}"
               ::"l"(p), "l"(((uint64_t)v.y << 32) | v.x), "l"(((uint64_t)v.w << 32) | v.z) : "memory");
}
__device__ __forceinline__ uint4 ld_tagged(const void* p) {
  uint64_t a, b;
  asm volatile("{\n.reg .b128 r;\nld.relaxed.gpu.global.b128 r, [%2];\nmov.b128 {%0, %1}, r;\n}" : "=l"(a), "=l"(b) : "l"(p) : "memory");
  return make_uint4((uint32_t)a, (uint32_t)(a >> 32), (uint32_t)b, (uint32_t)(b >> 32));
}
__device__ __forceinline__ void st_tagged64(void* p, uint32_t x, uint32_t y) {
  asm volatile("st.relaxed.gpu.global.b64 [%0], %1;" ::"l"(p), "l"(((uint64_t)y << 32) | x) : "memory");
}
__device__ __forceinline__ float2 ld_stats(const float2* p, uint32_t tag) {
  uint64_t a;
  uint32_t it = 0;
#pragma unroll 1
  do {
    asm volatile("ld.relaxed.gpu.global.b64 %0, [%1];" : "=l"(a) : "l"(p) : "memory");
  } while ((((uint32_t)a ^ tag) & 1u) && ++it < SPIN_LIMIT);
  return make_float2(__uint_as_float((uint32_t)a), __uint_as_float((uint32_t)(a >> 32)));
}
__device__ __forceinline__ uint32_t set_tag(uint32_t w, uint32_t tag) { return (w & 0xfffffffeu) | tag; }
__device__ __forceinline__ void st_tagged_f4(float4* p, float a, float b, float c, float d, uint32_t tag) {
  st_tagged(p, make_uint4(set_tag(__float_as_uint(a), tag), __float_as_uint(b), __float_as_uint(c), __float_as_uint(d)));
}

__device__ __forceinline__ void wgmma_ss240(float (&d)[120], uint32_t alo, uint32_t blo, uint32_t sc) {
  asm volatile("{\n.reg .pred p;\n.reg .b64 da, db;\n"
    "setp.ne.b32 p, %123, 0;\n"
    "mov.b64 da, {%120, %122};\nmov.b64 db, {%121, %122};\n"
    "wgmma.mma_async.sync.aligned.m64n240k16.f32.bf16.bf16 {%0, %1, %2, %3, %4, %5, %6, %7, %8, %9, %10, %11, %12, %13, %14, %15, %16, %17, %18, %19, %20, %21, %22, %23, %24, %25, %26, %27, %28, %29, %30, %31, %32, %33, %34, %35, %36, %37, %38, %39, %40, %41, %42, %43, %44, %45, %46, %47, %48, %49, %50, %51, %52, %53, %54, %55, %56, %57, %58, %59, %60, %61, %62, %63, %64, %65, %66, %67, %68, %69, %70, %71, %72, %73, %74, %75, %76, %77, %78, %79, %80, %81, %82, %83, %84, %85, %86, %87, %88, %89, %90, %91, %92, %93, %94, %95, %96, %97, %98, %99, %100, %101, %102, %103, %104, %105, %106, %107, %108, %109, %110, %111, %112, %113, %114, %115, %116, %117, %118, %119}, da, db, p, 1, 1, 0, 1;\n}\n"
    :
        "+f"(d[0]), "+f"(d[1]), "+f"(d[2]), "+f"(d[3]), "+f"(d[4]), "+f"(d[5]), "+f"(d[6]), "+f"(d[7]),
        "+f"(d[8]), "+f"(d[9]), "+f"(d[10]), "+f"(d[11]), "+f"(d[12]), "+f"(d[13]), "+f"(d[14]), "+f"(d[15]),
        "+f"(d[16]), "+f"(d[17]), "+f"(d[18]), "+f"(d[19]), "+f"(d[20]), "+f"(d[21]), "+f"(d[22]), "+f"(d[23]),
        "+f"(d[24]), "+f"(d[25]), "+f"(d[26]), "+f"(d[27]), "+f"(d[28]), "+f"(d[29]), "+f"(d[30]), "+f"(d[31]),
        "+f"(d[32]), "+f"(d[33]), "+f"(d[34]), "+f"(d[35]), "+f"(d[36]), "+f"(d[37]), "+f"(d[38]), "+f"(d[39]),
        "+f"(d[40]), "+f"(d[41]), "+f"(d[42]), "+f"(d[43]), "+f"(d[44]), "+f"(d[45]), "+f"(d[46]), "+f"(d[47]),
        "+f"(d[48]), "+f"(d[49]), "+f"(d[50]), "+f"(d[51]), "+f"(d[52]), "+f"(d[53]), "+f"(d[54]), "+f"(d[55]),
        "+f"(d[56]), "+f"(d[57]), "+f"(d[58]), "+f"(d[59]), "+f"(d[60]), "+f"(d[61]), "+f"(d[62]), "+f"(d[63]),
        "+f"(d[64]), "+f"(d[65]), "+f"(d[66]), "+f"(d[67]), "+f"(d[68]), "+f"(d[69]), "+f"(d[70]), "+f"(d[71]),
        "+f"(d[72]), "+f"(d[73]), "+f"(d[74]), "+f"(d[75]), "+f"(d[76]), "+f"(d[77]), "+f"(d[78]), "+f"(d[79]),
        "+f"(d[80]), "+f"(d[81]), "+f"(d[82]), "+f"(d[83]), "+f"(d[84]), "+f"(d[85]), "+f"(d[86]), "+f"(d[87]),
        "+f"(d[88]), "+f"(d[89]), "+f"(d[90]), "+f"(d[91]), "+f"(d[92]), "+f"(d[93]), "+f"(d[94]), "+f"(d[95]),
        "+f"(d[96]), "+f"(d[97]), "+f"(d[98]), "+f"(d[99]), "+f"(d[100]), "+f"(d[101]), "+f"(d[102]), "+f"(d[103]),
        "+f"(d[104]), "+f"(d[105]), "+f"(d[106]), "+f"(d[107]), "+f"(d[108]), "+f"(d[109]), "+f"(d[110]), "+f"(d[111]),
        "+f"(d[112]), "+f"(d[113]), "+f"(d[114]), "+f"(d[115]), "+f"(d[116]), "+f"(d[117]), "+f"(d[118]), "+f"(d[119])
    : "r"(alo), "r"(blo), "n"(DESC_HI), "r"(sc));
}
__device__ __forceinline__ void wgmma_ss128_init(float (&d)[64], uint32_t alo, uint32_t blo) {
  asm volatile("{\n.reg .pred p;\n.reg .b64 da, db;\n"
    "setp.ne.b32 p, 0, 0;\n"
    "mov.b64 da, {%64, %66};\nmov.b64 db, {%65, %66};\n"
    "wgmma.mma_async.sync.aligned.m64n128k16.f32.bf16.bf16 {%0, %1, %2, %3, %4, %5, %6, %7, %8, %9, %10, %11, %12, %13, %14, %15, %16, %17, %18, %19, %20, %21, %22, %23, %24, %25, %26, %27, %28, %29, %30, %31, %32, %33, %34, %35, %36, %37, %38, %39, %40, %41, %42, %43, %44, %45, %46, %47, %48, %49, %50, %51, %52, %53, %54, %55, %56, %57, %58, %59, %60, %61, %62, %63}, da, db, p, 1, 1, 0, 1;\n}\n"
    :
        "=f"(d[0]), "=f"(d[1]), "=f"(d[2]), "=f"(d[3]), "=f"(d[4]), "=f"(d[5]), "=f"(d[6]), "=f"(d[7]),
        "=f"(d[8]), "=f"(d[9]), "=f"(d[10]), "=f"(d[11]), "=f"(d[12]), "=f"(d[13]), "=f"(d[14]), "=f"(d[15]),
        "=f"(d[16]), "=f"(d[17]), "=f"(d[18]), "=f"(d[19]), "=f"(d[20]), "=f"(d[21]), "=f"(d[22]), "=f"(d[23]),
        "=f"(d[24]), "=f"(d[25]), "=f"(d[26]), "=f"(d[27]), "=f"(d[28]), "=f"(d[29]), "=f"(d[30]), "=f"(d[31]),
        "=f"(d[32]), "=f"(d[33]), "=f"(d[34]), "=f"(d[35]), "=f"(d[36]), "=f"(d[37]), "=f"(d[38]), "=f"(d[39]),
        "=f"(d[40]), "=f"(d[41]), "=f"(d[42]), "=f"(d[43]), "=f"(d[44]), "=f"(d[45]), "=f"(d[46]), "=f"(d[47]),
        "=f"(d[48]), "=f"(d[49]), "=f"(d[50]), "=f"(d[51]), "=f"(d[52]), "=f"(d[53]), "=f"(d[54]), "=f"(d[55]),
        "=f"(d[56]), "=f"(d[57]), "=f"(d[58]), "=f"(d[59]), "=f"(d[60]), "=f"(d[61]), "=f"(d[62]), "=f"(d[63])
    : "r"(alo), "r"(blo), "n"(DESC_HI));
}
__device__ __forceinline__ void wgmma_ss128(float (&d)[64], uint32_t alo, uint32_t blo) {
  asm volatile("{\n.reg .pred p;\n.reg .b64 da, db;\n"
    "setp.eq.b32 p, 0, 0;\n"
    "mov.b64 da, {%64, %66};\nmov.b64 db, {%65, %66};\n"
    "wgmma.mma_async.sync.aligned.m64n128k16.f32.bf16.bf16 {%0, %1, %2, %3, %4, %5, %6, %7, %8, %9, %10, %11, %12, %13, %14, %15, %16, %17, %18, %19, %20, %21, %22, %23, %24, %25, %26, %27, %28, %29, %30, %31, %32, %33, %34, %35, %36, %37, %38, %39, %40, %41, %42, %43, %44, %45, %46, %47, %48, %49, %50, %51, %52, %53, %54, %55, %56, %57, %58, %59, %60, %61, %62, %63}, da, db, p, 1, 1, 0, 1;\n}\n"
    :
        "+f"(d[0]), "+f"(d[1]), "+f"(d[2]), "+f"(d[3]), "+f"(d[4]), "+f"(d[5]), "+f"(d[6]), "+f"(d[7]),
        "+f"(d[8]), "+f"(d[9]), "+f"(d[10]), "+f"(d[11]), "+f"(d[12]), "+f"(d[13]), "+f"(d[14]), "+f"(d[15]),
        "+f"(d[16]), "+f"(d[17]), "+f"(d[18]), "+f"(d[19]), "+f"(d[20]), "+f"(d[21]), "+f"(d[22]), "+f"(d[23]),
        "+f"(d[24]), "+f"(d[25]), "+f"(d[26]), "+f"(d[27]), "+f"(d[28]), "+f"(d[29]), "+f"(d[30]), "+f"(d[31]),
        "+f"(d[32]), "+f"(d[33]), "+f"(d[34]), "+f"(d[35]), "+f"(d[36]), "+f"(d[37]), "+f"(d[38]), "+f"(d[39]),
        "+f"(d[40]), "+f"(d[41]), "+f"(d[42]), "+f"(d[43]), "+f"(d[44]), "+f"(d[45]), "+f"(d[46]), "+f"(d[47]),
        "+f"(d[48]), "+f"(d[49]), "+f"(d[50]), "+f"(d[51]), "+f"(d[52]), "+f"(d[53]), "+f"(d[54]), "+f"(d[55]),
        "+f"(d[56]), "+f"(d[57]), "+f"(d[58]), "+f"(d[59]), "+f"(d[60]), "+f"(d[61]), "+f"(d[62]), "+f"(d[63])
    : "r"(alo), "r"(blo), "n"(DESC_HI));
}
__device__ __forceinline__ void wgmma_rs64_init(float (&d)[32], uint32_t a0, uint32_t a1, uint32_t a2, uint32_t a3, uint32_t blo) {
  asm volatile("{\n.reg .pred p;\n.reg .b64 db;\n"
    "setp.ne.b32 p, 0, 0;\n"
    "mov.b64 db, {%36, %37};\n"
    "wgmma.mma_async.sync.aligned.m64n64k16.f32.bf16.bf16 {%0, %1, %2, %3, %4, %5, %6, %7, %8, %9, %10, %11, %12, %13, %14, %15, %16, %17, %18, %19, %20, %21, %22, %23, %24, %25, %26, %27, %28, %29, %30, %31}, {%32,%33,%34,%35}, db, p, 1, 1, 1;\n}\n"
    :
        "=f"(d[0]), "=f"(d[1]), "=f"(d[2]), "=f"(d[3]), "=f"(d[4]), "=f"(d[5]), "=f"(d[6]), "=f"(d[7]),
        "=f"(d[8]), "=f"(d[9]), "=f"(d[10]), "=f"(d[11]), "=f"(d[12]), "=f"(d[13]), "=f"(d[14]), "=f"(d[15]),
        "=f"(d[16]), "=f"(d[17]), "=f"(d[18]), "=f"(d[19]), "=f"(d[20]), "=f"(d[21]), "=f"(d[22]), "=f"(d[23]),
        "=f"(d[24]), "=f"(d[25]), "=f"(d[26]), "=f"(d[27]), "=f"(d[28]), "=f"(d[29]), "=f"(d[30]), "=f"(d[31])
    : "r"(a0), "r"(a1), "r"(a2), "r"(a3), "r"(blo), "n"(DESC_HI));
}
__device__ __forceinline__ void wgmma_rs64(float (&d)[32], uint32_t a0, uint32_t a1, uint32_t a2, uint32_t a3, uint32_t blo) {
  asm volatile("{\n.reg .pred p;\n.reg .b64 db;\n"
    "setp.eq.b32 p, 0, 0;\n"
    "mov.b64 db, {%36, %37};\n"
    "wgmma.mma_async.sync.aligned.m64n64k16.f32.bf16.bf16 {%0, %1, %2, %3, %4, %5, %6, %7, %8, %9, %10, %11, %12, %13, %14, %15, %16, %17, %18, %19, %20, %21, %22, %23, %24, %25, %26, %27, %28, %29, %30, %31}, {%32,%33,%34,%35}, db, p, 1, 1, 1;\n}\n"
    :
        "+f"(d[0]), "+f"(d[1]), "+f"(d[2]), "+f"(d[3]), "+f"(d[4]), "+f"(d[5]), "+f"(d[6]), "+f"(d[7]),
        "+f"(d[8]), "+f"(d[9]), "+f"(d[10]), "+f"(d[11]), "+f"(d[12]), "+f"(d[13]), "+f"(d[14]), "+f"(d[15]),
        "+f"(d[16]), "+f"(d[17]), "+f"(d[18]), "+f"(d[19]), "+f"(d[20]), "+f"(d[21]), "+f"(d[22]), "+f"(d[23]),
        "+f"(d[24]), "+f"(d[25]), "+f"(d[26]), "+f"(d[27]), "+f"(d[28]), "+f"(d[29]), "+f"(d[30]), "+f"(d[31])
    : "r"(a0), "r"(a1), "r"(a2), "r"(a3), "r"(blo), "n"(DESC_HI));
}

template <int B>
__device__ __forceinline__ void qkv_piece(const float (&acc)[120], float2 s1, float2 s2, uint32_t cs_addr, uint2* gp) {
  const float2 c0 = lds64f(cs_addr + (16 * B) * 4), c1 = lds64f(cs_addr + (16 * B + 8) * 4);
  uint2 w1, w2;
  w1.x = pack_bf16(s1.x * fmaf(s1.y, c0.x, acc[8 * B + 0]), s1.x * fmaf(s1.y, c0.y, acc[8 * B + 1]));
  w2.x = pack_bf16(s2.x * fmaf(s2.y, c0.x, acc[8 * B + 2]), s2.x * fmaf(s2.y, c0.y, acc[8 * B + 3]));
  w1.y = pack_bf16(s1.x * fmaf(s1.y, c1.x, acc[8 * B + 4]), s1.x * fmaf(s1.y, c1.y, acc[8 * B + 5]));
  w2.y = pack_bf16(s2.x * fmaf(s2.y, c1.x, acc[8 * B + 6]), s2.x * fmaf(s2.y, c1.y, acc[8 * B + 7]));
  __stcg(gp + B * BLK, w1);
  __stcg(gp + B * BLK + 32, w2);
}
__device__ __forceinline__ float swiglu(float ag, float au, float cg, float cu, const float3 s) {
  const float g = fmaf(s.y, cg, ag), u = fmaf(s.y, cu, au);
  const float e = ex2f(g * s.x);
  return (g * u) * rcpf(fmaf(e, s.z, s.z));
}
template <int NB>
__device__ __forceinline__ void gu_piece(const float (&acc)[64], const float3 s1, const float3 s2, uint32_t cs_addr, uint32_t (&h)[16]) {
  const float2 cg = lds64f(cs_addr + (8 * NB) * 4), cu = lds64f(cs_addr + (64 + 8 * NB) * 4);
  h[4 * (NB >> 1) + 2 * (NB & 1) + 0] = pack_bf16(swiglu(acc[4 * NB + 0], acc[32 + 4 * NB + 0], cg.x, cu.x, s1),
                                                  swiglu(acc[4 * NB + 1], acc[32 + 4 * NB + 1], cg.y, cu.y, s1));
  h[4 * (NB >> 1) + 2 * (NB & 1) + 1] = pack_bf16(swiglu(acc[4 * NB + 2], acc[32 + 4 * NB + 2], cg.x, cu.x, s2),
                                                  swiglu(acc[4 * NB + 3], acc[32 + 4 * NB + 3], cg.y, cu.y, s2));
}

struct AttnOps { uint2 q1[5], q2[5], k[3][5], v[3][5]; };
__device__ __forceinline__ void attn_load(AttnOps& o, int j, int w, int half0, int g, int t) {
  const uint2* qb = g_qkv + (5 * j) * BLK + w * 4096 + t;
  const uint2* qp = qb + (half0 + g) * 4;
  const uint2* kp0 = qb + 40 * BLK + max(half0 - 7 + g, 0) * 4;
  const uint2* kp1 = qb + 40 * BLK + (half0 + 1 + g) * 4;
  const uint2* kp2 = qb + 40 * BLK + (half0 + min(9 + g, 15)) * 4;
#pragma unroll
  for (int b = 0; b < 5; b++) {
    o.q1[b] = __ldcg(qp + b * BLK);
    o.q2[b] = __ldcg(qp + b * BLK + 32);
    o.k[0][b] = __ldcg(kp0 + b * BLK); o.k[1][b] = __ldcg(kp1 + b * BLK); o.k[2][b] = __ldcg(kp2 + b * BLK);
  }
#pragma unroll
  for (int b = 0; b < 5; b++) {
    o.v[0][b] = __ldcg(kp0 + (40 + b) * BLK); o.v[1][b] = __ldcg(kp1 + (40 + b) * BLK); o.v[2][b] = __ldcg(kp2 + (40 + b) * BLK);
  }
}
template <int H>
__device__ __forceinline__ void attn_scores(const AttnOps& o, uint32_t mlo, bool p0, bool p1, float bias0, float bias1, uint32_t pm,
                                            uint32_t (&P)[4]) {
  const uint32_t mhi = ~mlo;
  const uint32_t m0l = (H == 0) ? 0xffffffffu : (H == 1) ? mhi : 0u;
  const uint32_t m0h = (H == 3) ? mhi : 0xffffffffu;
  const uint32_t m1l = (H == 0) ? mlo : 0xffffffffu;
  const uint32_t m1h = (H == 2) ? mlo : (H == 3) ? 0xffffffffu : 0u;
  float s[3][4];
#pragma unroll
  for (int kb = 0; kb < 3; kb++) {
    s[kb][0] = s[kb][1] = s[kb][2] = s[kb][3] = 0.f;
    mma16816(s[kb], o.q1[H].x & m0l, o.q2[H].x & m0l, o.q1[H].y & m0h, o.q2[H].y & m0h, o.k[kb][H].x, o.k[kb][H].y);
    mma16816(s[kb], o.q1[H + 1].x & m1l, o.q2[H + 1].x & m1l, o.q1[H + 1].y & m1h, o.q2[H + 1].y & m1h, o.k[kb][H + 1].x, o.k[kb][H + 1].y);
  }
  const float a0 = (p0 ? s[0][0] : s[1][0]) + bias0, a1 = (p1 ? s[0][1] : s[1][1]) + bias1;
  const float b0 = p0 ? s[1][2] : s[2][2], b1 = p1 ? s[1][3] : s[2][3];
  float m1 = fmaxf(a0, a1), m2 = fmaxf(b0, b1);
  m1 = fmaxf(m1, __shfl_xor_sync(0xffffffffu, m1, 1)); m2 = fmaxf(m2, __shfl_xor_sync(0xffffffffu, m2, 1));
  m1 = fmaxf(m1, __shfl_xor_sync(0xffffffffu, m1, 2)); m2 = fmaxf(m2, __shfl_xor_sync(0xffffffffu, m2, 2));
  const float cexp = 0.22360679774997896f * 1.4426950408889634f;
  const float o1 = -m1 * cexp, o2 = -m2 * cexp;
  const float e0 = ex2f(fmaf(a0, cexp, o1)), e1 = ex2f(fmaf(a1, cexp, o1));
  const float f0 = ex2f(fmaf(b0, cexp, o2)), f1 = ex2f(fmaf(b1, cexp, o2));
  float l1 = e0 + e1, l2 = f0 + f1;
  l1 += __shfl_xor_sync(0xffffffffu, l1, 1); l2 += __shfl_xor_sync(0xffffffffu, l2, 1);
  l1 += __shfl_xor_sync(0xffffffffu, l1, 2); l2 += __shfl_xor_sync(0xffffffffu, l2, 2);
  const float i1 = rcpf(l1), i2 = rcpf(l2);
  const uint32_t w1 = pack_bf16(e0 * i1, e1 * i1), w2 = pack_bf16(f0 * i2, f1 * i2);
  P[0] = w1 & pm;  P[1] = w1 & ~pm;
  P[2] = w2 & pm;  P[3] = w2 & ~pm;
}
__device__ __forceinline__ void attn_pv(const uint32_t (&P)[4], uint32_t v0, uint32_t v1, uint32_t v2, uint32_t& w1, uint32_t& w2) {
  float o[4] = {0.f, 0.f, 0.f, 0.f};
  mma16816(o, P[0], 0u, P[1], P[2], v0, v1);
  mma1688(o, 0u, P[3], v2);
  w1 = pack_bf16(o[0], o[1]);
  w2 = pack_bf16(o[2], o[3]);
}
__device__ __forceinline__ void attn_compute(const AttnOps& o, int half0, int g, int t, uint32_t (&of)[20]) {
  const bool lo = t < 2;
  const uint32_t mlo = lo ? 0xffffffffu : 0u;
  const bool p0 = 2 * t >= g, p1 = 2 * t + 1 >= g;
  const uint32_t pm = (p0 ? 0x0000ffffu : 0u) | (p1 ? 0xffff0000u : 0u);
  const float bias0 = (p0 && half0 - 7 + 2 * t < 0) ? -INFINITY : 0.f, bias1 = (p1 && half0 - 6 + 2 * t < 0) ? -INFINITY : 0.f;
  uint32_t P0[4], P1[4], P2[4], P3[4];
  attn_scores<0>(o, mlo, p0, p1, bias0, bias1, pm, P0);
  attn_scores<1>(o, mlo, p0, p1, bias0, bias1, pm, P1);
  attn_scores<2>(o, mlo, p0, p1, bias0, bias1, pm, P2);
  attn_scores<3>(o, mlo, p0, p1, bias0, bias1, pm, P3);
  uint32_t c1, c2;
  attn_pv(P0, movm(o.v[0][0].x), movm(o.v[1][0].x), movm(o.v[2][0].x), of[0], of[1]);
  attn_pv(P0, movm(o.v[0][0].y), movm(o.v[1][0].y), movm(o.v[2][0].y), of[2], of[3]);
  {
    const uint32_t t0 = movm(o.v[0][1].x), t1 = movm(o.v[1][1].x), t2 = movm(o.v[2][1].x);
    attn_pv(P0, t0, t1, t2, of[4], of[5]);
    attn_pv(P1, t0, t1, t2, c1, c2);
    of[4] = lo ? of[4] : c1; of[5] = lo ? of[5] : c2;
  }
  attn_pv(P1, movm(o.v[0][1].y), movm(o.v[1][1].y), movm(o.v[2][1].y), of[6], of[7]);
  attn_pv(P1, movm(o.v[0][2].x), movm(o.v[1][2].x), movm(o.v[2][2].x), of[8], of[9]);
  attn_pv(P2, movm(o.v[0][2].y), movm(o.v[1][2].y), movm(o.v[2][2].y), of[10], of[11]);
  attn_pv(P2, movm(o.v[0][3].x), movm(o.v[1][3].x), movm(o.v[2][3].x), of[12], of[13]);
  {
    const uint32_t t0 = movm(o.v[0][3].y), t1 = movm(o.v[1][3].y), t2 = movm(o.v[2][3].y);
    attn_pv(P2, t0, t1, t2, of[14], of[15]);
    attn_pv(P3, t0, t1, t2, c1, c2);
    of[14] = lo ? of[14] : c1; of[15] = lo ? of[15] : c2;
  }
  attn_pv(P3, movm(o.v[0][4].x), movm(o.v[1][4].x), movm(o.v[2][4].x), of[16], of[17]);
  attn_pv(P3, movm(o.v[0][4].y), movm(o.v[1][4].y), movm(o.v[2][4].y), of[18], of[19]);
}

__device__ __forceinline__ void add8(float (&a)[8], const uint4 v) {
  a[0] += bf_lo(v.x); a[1] += bf_hi(v.x); a[2] += bf_lo(v.y); a[3] += bf_hi(v.y);
  a[4] += bf_lo(v.z); a[5] += bf_hi(v.z); a[6] += bf_lo(v.w); a[7] += bf_hi(v.w);
}
__device__ __forceinline__ void row_stats(const uint4 (&v)[5], int row, int lane, uint32_t tag) {
  float s = 0.f;
#pragma unroll
  for (int q = 0; q < 5; q++) {
    const uint4 u = v[q];
    s += (bf_lo(u.x) + bf_hi(u.x)) + (bf_lo(u.y) + bf_hi(u.y)) + (bf_lo(u.z) + bf_hi(u.z)) + (bf_lo(u.w) + bf_hi(u.w));
  }
#pragma unroll
  for (int o = 1; o < 16; o <<= 1) s += __shfl_xor_sync(0xffffffffu, s, o);
  const float mu = s * (1.0f / D_);
  float q2 = 0.f, q3 = 0.f;
#pragma unroll
  for (int q = 0; q < 5; q++) {
    const uint4 u = v[q];
    float d;
    d = bf_lo(u.x) - mu; q2 = fmaf(d, d, q2); d = bf_hi(u.x) - mu; q3 = fmaf(d, d, q3);
    d = bf_lo(u.y) - mu; q2 = fmaf(d, d, q2); d = bf_hi(u.y) - mu; q3 = fmaf(d, d, q3);
    d = bf_lo(u.z) - mu; q2 = fmaf(d, d, q2); d = bf_hi(u.z) - mu; q3 = fmaf(d, d, q3);
    d = bf_lo(u.w) - mu; q2 = fmaf(d, d, q2); d = bf_hi(u.w) - mu; q3 = fmaf(d, d, q3);
  }
  q2 += q3;
#pragma unroll
  for (int o = 1; o < 16; o <<= 1) q2 += __shfl_xor_sync(0xffffffffu, q2, o);
  const float r = rsqrtf(q2 * (1.0f / D_) + 1e-5f);
  if ((lane & 15) == 0) st_tagged64(&g_stats[row], set_tag(__float_as_uint(r), tag), __float_as_uint(-mu));
}
template <int LOG2C>
__device__ __forceinline__ void col_reduce_store(float (&a)[8], int lane, bool active, float4* dst, uint32_t tag) {
#pragma unroll
  for (int o = 1 << LOG2C; o < 32; o <<= 1)
#pragma unroll
    for (int i = 0; i < 8; i++) a[i] += __shfl_xor_sync(0xffffffffu, a[i], o);
  if (lane < (1 << LOG2C) && active) {
    st_tagged_f4(dst, a[0], a[1], a[2], a[3], tag);
    st_tagged_f4(dst + 1, a[4], a[5], a[6], a[7], tag);
  }
}
__device__ __forceinline__ void col_gather16(int j, int i0, int iend, int lane, uint32_t cs_smem, uint32_t tag) {
  uint4 v[2][4];
  int i4[2];
  uint32_t it = 0;
#pragma unroll
  for (int u = 0; u < 2; u++) i4[u] = min(i0 + 8 * u + (lane >> 2), iend - 1);
#pragma unroll 1
  while (true) {
    uint32_t bad = 0;
#pragma unroll
    for (int u = 0; u < 2; u++) {
      const float4* p = &g_cs[(j * 16 + 4 * (lane & 3)) * 160 + i4[u]];
#pragma unroll
      for (int m = 0; m < 4; m++) { v[u][m] = ld_tagged(p + 160 * m); bad |= v[u][m].x ^ tag; }
    }
    if (!__any_sync(0xffffffffu, bad & 1u) || ++it > SPIN_LIMIT) break;
  }
#pragma unroll
  for (int u = 0; u < 2; u++) {
    float4 s;
    s.x = (__uint_as_float(v[u][0].x) + __uint_as_float(v[u][1].x)) + (__uint_as_float(v[u][2].x) + __uint_as_float(v[u][3].x));
    s.y = (__uint_as_float(v[u][0].y) + __uint_as_float(v[u][1].y)) + (__uint_as_float(v[u][2].y) + __uint_as_float(v[u][3].y));
    s.z = (__uint_as_float(v[u][0].z) + __uint_as_float(v[u][1].z)) + (__uint_as_float(v[u][2].z) + __uint_as_float(v[u][3].z));
    s.w = (__uint_as_float(v[u][0].w) + __uint_as_float(v[u][1].w)) + (__uint_as_float(v[u][2].w) + __uint_as_float(v[u][3].w));
#pragma unroll
    for (int o = 1; o < 4; o <<= 1) {
      s.x += __shfl_xor_sync(0xffffffffu, s.x, o); s.y += __shfl_xor_sync(0xffffffffu, s.y, o);
      s.z += __shfl_xor_sync(0xffffffffu, s.z, o); s.w += __shfl_xor_sync(0xffffffffu, s.w, o);
    }
    if ((lane & 3) == 0) sts128f(cs_smem + i4[u] * 16, s);
  }
}

template <bool INIT>
__device__ __forceinline__ void g2_h(float (&acc)[32], const uint32_t (&h)[16], uint32_t blo) {
  if (INIT) wgmma_rs64_init(acc, h[0], h[1], h[2], h[3], blo);
  else      wgmma_rs64(acc, h[0], h[1], h[2], h[3], blo);
  wgmma_rs64(acc, h[4], h[5], h[6], h[7], blo + 128);
  wgmma_rs64(acc, h[8], h[9], h[10], h[11], blo + 256);
  wgmma_rs64(acc, h[12], h[13], h[14], h[15], blo + 384);
}
__device__ __forceinline__ void g2_o(float (&acc)[32], const uint32_t (&o)[20], uint32_t blo) {
#pragma unroll
  for (int s = 0; s < 5; s++) wgmma_rs64(acc, o[4 * s], o[4 * s + 1], o[4 * s + 2], o[4 * s + 3], blo + 1536 + 128 * s);
}
__device__ __forceinline__ uint4 pack8(const float (&acc)[32], int v) {
  return make_uint4(pack_bf16(acc[8 * v + 0], acc[8 * v + 1]), pack_bf16(acc[8 * v + 2], acc[8 * v + 3]),
                    pack_bf16(acc[8 * v + 4], acc[8 * v + 5]), pack_bf16(acc[8 * v + 6], acc[8 * v + 7]));
}
__device__ __forceinline__ void pair_send(const float (&acc)[32], uint32_t peer_buf, uint32_t peer_bar) {
#pragma unroll
  for (int v = 0; v < 4; v++) st_async(peer_buf + v * 2048, pack8(acc, v), peer_bar);
}
__device__ __forceinline__ uint32_t add_bf16x2(uint32_t a, uint32_t b) {
  uint32_t r;
  asm("add.rn.bf16x2 %0, %1, %2;" : "=r"(r) : "r"(a), "r"(b));
  return r;
}
__device__ __forceinline__ void pair_add_store(const uint4 (&kp)[4], uint32_t buf, uint4* dst, uint32_t tag) {
#pragma unroll
  for (int v = 0; v < 4; v++) {
    const uint4 u = lds128(buf + v * 2048);
    st_tagged(dst + v * 512, make_uint4(set_tag(add_bf16x2(kp[v].x, u.x), tag), add_bf16x2(kp[v].y, u.y),
                                        add_bf16x2(kp[v].z, u.z), add_bf16x2(kp[v].w, u.w)));
  }
}
struct Red { uint4 p[4]; uint32_t x[4]; };
constexpr int ROW2 = 16 * (D_ / 2);
__device__ __forceinline__ void red_load(Red& r, const uint4* src, const uint32_t* xp) {
#pragma unroll
  for (int s = 0; s < 4; s++) r.p[s] = ld_tagged(src + s * 128);
  r.x[0] = __ldg(xp); r.x[1] = __ldg(xp + ROW2); r.x[2] = __ldg(xp + 4); r.x[3] = __ldg(xp + 4 + ROW2);
}
__device__ __forceinline__ void red_finish(Red& r, const uint4* src, uint32_t* op, uint32_t tag) {
  uint32_t it = 0;
#pragma unroll 1
  while ((((r.p[0].x ^ tag) | (r.p[1].x ^ tag) | (r.p[2].x ^ tag) | (r.p[3].x ^ tag)) & 1u) && ++it < SPIN_LIMIT) {
#pragma unroll
    for (int s = 0; s < 4; s++) r.p[s] = ld_tagged(src + s * 128);
  }
  float a[8];
  a[0] = bf_lo(r.x[0]); a[1] = bf_hi(r.x[0]); a[2] = bf_lo(r.x[1]); a[3] = bf_hi(r.x[1]);
  a[4] = bf_lo(r.x[2]); a[5] = bf_hi(r.x[2]); a[6] = bf_lo(r.x[3]); a[7] = bf_hi(r.x[3]);
#pragma unroll
  for (int s = 0; s < 4; s++) add8(a, r.p[s]);
  op[0] = pack_bf16(a[0], a[1]);
  op[ROW2] = pack_bf16(a[2], a[3]);
  op[4] = pack_bf16(a[4], a[5]);
  op[4 + ROW2] = pack_bf16(a[6], a[7]);
}

__global__ void __launch_bounds__(NTHREADS, 1)
fused_kernel(const __grid_constant__ CUtensorMap tmX, const __grid_constant__ CUtensorMap tmQ3,
             const __grid_constant__ CUtensorMap tmQ1, const __grid_constant__ CUtensorMap tmW1,
             const __grid_constant__ CUtensorMap tmW3, const __grid_constant__ CUtensorMap tmW2,
             const __grid_constant__ CUtensorMap tmWo, const Params prm) {
  extern __shared__ __align__(1024) uint8_t smem_raw[];
  const uint32_t sb = smem_u32(smem_raw);
  const uint32_t bar0 = sb + SM_BAR;
  const int tid = threadIdx.x;
  const int warp = __shfl_sync(0xffffffffu, tid >> 5, 0);
  const int lane = tid & 31;
  const int j = blockIdx.x & 7, mt = blockIdx.x >> 3;
#define BAR(i) (bar0 + 8 * (i))

  {
    const int r = tid & 127;
    const __nv_bfloat16* p = (tid < 256) ? prm.x + (size_t)(128 * mt + r) * D_ + 64 * (tid >> 7)
                                         : prm.wqkv + (size_t)(r >> 1) * NQKV + 240 * j + 128 * (r & 1);
    asm volatile("prefetch.global.L2 [%0];" ::"l"(p));
    if (tid >= 256) asm volatile("prefetch.global.L2 [%0];" ::"l"(p + 64));
  }
  if (tid == 0) {
    TSTAMP(0); GSTAMP(62);
    prefetch_tmap(&tmX); prefetch_tmap(&tmQ3); prefetch_tmap(&tmQ1);
    for (int i = 0; i < 10; i++) mbar_init(BAR(B_XFULL + i), 1);
    for (int i = 0; i < 4; i++) { mbar_init(BAR(B_FULL + i), 1); mbar_init(BAR(B_EMPTY + i), 2); }
    for (int i = 0; i < 6; i++) mbar_init(BAR(B_CFULL + i), 1);
    for (int i = 0; i < 4; i++) mbar_init(BAR(B_CEMPTY + i), 2);
    mbar_init(BAR(B_EPI), 1); mbar_init(BAR(B_GU), 1);
    mbar_init(BAR(B_QKVDONE), 8); mbar_init(BAR(B_QKVRDY), 1);
    for (int i = 0; i < 10; i++) { mbar_init(BAR(B_RFULL + i), 1); mbar_init(BAR(B_REMPTY + i), 4); }
    asm volatile("fence.mbarrier_init.release.cluster;" ::: "memory");
    asm volatile("fence.proxy.async.shared::cta;" ::: "memory");
    TSTAMP(4);
    for (int i = 0; i < 10; i++) mbar_expect_tx(BAR(B_RFULL + i), 8192);
#pragma unroll 1
    for (int ks = 0; ks < 4; ks++) {
      if ((ks & 1) == 0) {
        mbar_expect_tx(BAR(B_XFULL + (ks >> 1)), SLOT);
        tma3d(sb + SM_X + (ks >> 1) * SLOT, &tmX, 32 * ks, 64 * mt, 0, BAR(B_XFULL + (ks >> 1)));
      }
      mbar_expect_tx(BAR(B_FULL + ks), SLOT);
      tma3d(sb + SM_RING + ks * SLOT, &tmQ3, 240 * j, 32 * ks, 0, BAR(B_FULL + ks));
      tma2d(sb + SM_RING + ks * SLOT + 12288, &tmQ1, 240 * j + 192, 32 * ks, BAR(B_FULL + ks));
    }
    mbar_expect_tx(BAR(B_XFULL + 2), SLOT);
    tma3d(sb + SM_X + 2 * SLOT, &tmX, 128, 64 * mt, 0, BAR(B_XFULL + 2));
    TSTAMP(5);
  }
  __syncthreads();
  asm volatile("barrier.cluster.arrive.release.aligned;" ::: "memory");

  if (warp < 4) {
    asm volatile("setmaxnreg.dec.sync.aligned.u32 56;");
    if (warp == 0) {
      if (lane == 0) {
        const uint32_t ring = sb + SM_RING;
        prefetch_tmap(&tmW1); prefetch_tmap(&tmW3); prefetch_tmap(&tmW2); prefetch_tmap(&tmWo);
#pragma unroll 1
        for (int ks = 4; ks < 20; ks++) {
          if ((ks & 1) == 0 && ks < 18) {
            const int c = (ks >> 1) + 1;
            mbar_expect_tx(BAR(B_XFULL + c), SLOT);
            tma3d(sb + SM_X + c * SLOT, &tmX, 64 * c, 64 * mt, 0, BAR(B_XFULL + c));
          }
          const int s = ks & 3;
          mbar_wait(BAR(B_EMPTY + s), ((ks >> 2) & 1) ^ 1);
          mbar_expect_tx(BAR(B_FULL + s), SLOT);
          tma3d(ring + s * SLOT, &tmQ3, 240 * j, 32 * ks, 0, BAR(B_FULL + s));
          tma2d(ring + s * SLOT + 12288, &tmQ1, 240 * j + 192, 32 * ks, BAR(B_FULL + s));
        }
        TSTAMP(1);
#pragma unroll 1
        for (int g = 20; g < 50; g++) {
          const int s = g & 3, i = (g - 20) / 10, ks = (g - 20) - 10 * i;
          mbar_wait(BAR(B_EMPTY + s), ((g >> 2) & 1) ^ 1);
          mbar_expect_tx(BAR(B_FULL + s), SLOT);
          tma2d(ring + s * SLOT, &tmW1, 192 * j + 64 * i, 64 * ks, BAR(B_FULL + s));
          tma2d(ring + s * SLOT + 8192, &tmW3, 192 * j + 64 * i, 64 * ks, BAR(B_FULL + s));
        }
        TSTAMP(2);
#pragma unroll 1
        for (int c = 0; c < 10; c++) {
          if (c == 2) mbar_wait(BAR(B_EMPTY + 0), 0);
          if (c == 4) mbar_wait(BAR(B_EMPTY + 1), 0);
          const int s = c < 6 ? c : c - 6;
          if (c >= 6) mbar_wait(BAR(B_CEMPTY + s), 0);
          const uint32_t dst = sb + s * CSLOT;
          mbar_expect_tx(BAR(B_CFULL + s), CSLOT);
          tma2d(dst, &tmW2, 64 * c, 192 * j, BAR(B_CFULL + s));
          tma2d(dst + 24576, &tmWo, 64 * c, 80 * j, BAR(B_CFULL + s));
        }
        TSTAMP(3);
      }
    } else {
      unsigned epoch = 0;
      if (lane == 0) epoch = __ldcg(&g_flags[FL_DONE * 32]) >> 7;
      epoch = __shfl_sync(0xffffffffu, epoch, 0) + 1;
      const uint32_t cs_smem = sb + SM_CS;
      const uint32_t tag = epoch & 1u;
      if (warp == 1) {
        mbar_wait(BAR(B_XFULL + 5), 0);
#pragma unroll 1
        for (int i0 = 0; i0 < 60; i0 += 16) col_gather16(j, i0, 60, lane, cs_smem, tag);
        __syncwarp();
        if (lane == 0) { mbar_arrive(BAR(B_EPI)); TSTAMP(9); }
      } else if (warp == 2) {
        mbar_wait(BAR(B_XFULL + 9), 0);
#pragma unroll 1
        for (int i0 = 60; i0 < 156; i0 += 16) col_gather16(j, i0, 156, lane, cs_smem, tag);
        __syncwarp();
        if (lane == 0) { mbar_arrive(BAR(B_GU)); TSTAMP(15); }
      } else {
        if (lane == 0) {
          mbar_wait(BAR(B_QKVDONE), 0);
          TSTAMP(18);
          flag_signal(&g_flags[(FL_QKV + mt) * 32]);
        }
        __syncwarp();
        for (int i = lane; i < 170; i += 32) {
          const int r = 17 * mt + i / 10;
          const __nv_bfloat16* p = (r < 192 ? prm.w2 + (size_t)(192 * j + r) * D_ : prm.wo + (size_t)(80 * j + r - 192) * D_) + 64 * (i % 10);
          asm volatile("prefetch.global.L2 [%0];" ::"l"(p));
        }
        if (lane == 0) {
          flag_wait(&g_flags[(FL_QKV + mt) * 32], 8 * epoch);
          if (mt > 0) flag_wait(&g_flags[(FL_QKV + mt - 1) * 32], 8 * epoch);
          mbar_arrive(BAR(B_QKVRDY));
          TSTAMP(19);
        }
      }
    }
    __syncwarp();
    asm volatile("barrier.cluster.wait.acquire.aligned;" ::: "memory");
  } else {
    asm volatile("setmaxnreg.inc.sync.aligned.u32 224;");
    const int w = (warp >> 2) - 1;
    const int tau = tid & 127;
    const int g = lane >> 2, t = lane & 3;
    const int half0 = 64 * mt + 16 * (warp & 3);
    const int R1 = 2 * (half0 + g) + w;
    const bool elect = tau == 0;
    const uint32_t xlo = (((sb + SM_X + w * 8192) & 0x3FFFFu) >> 4) | (1u << 16);
    const uint32_t ringq = (((sb + SM_RING) & 0x3FFFFu) >> 4) | (256u << 16);
    const uint32_t ringg = (((sb + SM_RING) & 0x3FFFFu) >> 4) | (512u << 16);
    const uint32_t cs_addr = sb + SM_CS + t * 8;
    const uint32_t tag = ((__ldcg(&g_flags[FL_DONE * 32]) >> 7) + 1) & 1u;

    const int cw = warp - 4;
    const int srow = 128 * mt + 16 * j + 2 * cw + (lane >> 4);
    const bool act = cw < 7 || t < 2;
    uint4 xv[5], cv[10];

    if (elect && w == 0) TSTAMP(6);
    float accq[120];
#pragma unroll
    for (int i = 0; i < 120; i++) accq[i] = 0.f;
    fence_regs(accq);
#define Q_STAGES(K0, K1)                                                                          \
    _Pragma("unroll 1")                                                                           \
    for (int ks = (K0); ks < (K1); ks++) {                                                        \
      const int s = ks & 3;                                                                       \
      if ((ks & 1) == 0) mbar_wait(BAR(B_XFULL + (ks >> 1)), 0);                                  \
      if (ks == 0 && elect && w == 0) TSTAMP(7);                                                  \
      mbar_wait(BAR(B_FULL + s), (ks >> 2) & 1);                                                  \
      if (ks == 0 && elect && w == 0) TSTAMP(24);                                                 \
      wg_fence();                                                                                 \
      const uint32_t a = xlo + (ks >> 1) * 1024 + (ks & 1) * 4, b = ringq + s * 1024;             \
      wgmma_ss240(accq, a, b, 1);                                                                 \
      wgmma_ss240(accq, a + 2, b + 128, 1);                                                       \
      wg_commit();                                                                                \
      wg_wait<1>();                                                                               \
      if (ks > 0 && elect) mbar_arrive(BAR(B_EMPTY + ((ks - 1) & 3)));                            \
    }
    Q_STAGES(0, 3)
    if (elect && w == 0) TSTAMP(10);
    {
      const uint4* rp = reinterpret_cast<const uint4*>(prm.x + (size_t)srow * D_) + (lane & 15);
#pragma unroll
      for (int q = 0; q < 5; q++) xv[q] = __ldg(rp + 16 * q);
    }
    Q_STAGES(3, 5)
    {
      const __nv_bfloat16* cp = prm.wqkv + (size_t)(40 * mt + 5 * g) * NQKV + 240 * j + (act ? 32 * cw + 8 * t : 0);
#pragma unroll
      for (int q = 0; q < 5; q++) cv[q] = __ldg(reinterpret_cast<const uint4*>(cp + (size_t)q * NQKV));
    }
    if (elect && w == 0) TSTAMP(11);
    Q_STAGES(5, 10)
    if (elect && w == 0) TSTAMP(12);
    {
      row_stats(xv, srow, lane, tag);
      float a[8];
#pragma unroll
      for (int i = 0; i < 8; i++) a[i] = 0.f;
#pragma unroll
      for (int q = 0; q < 5; q++) add8(a, cv[q]);
      col_reduce_store<2>(a, lane, act, g_cs + (j * 16 + mt) * 160 + 8 * cw + 2 * t, tag);
      if (cw < 6) {
        const __nv_bfloat16* p = ((cw & 1) ? prm.w3 : prm.w1) + (size_t)(40 * mt + 10 * (lane >> 3)) * F_ + 192 * j + 64 * (cw >> 1) + 8 * (lane & 7);
#pragma unroll
        for (int q = 0; q < 10; q++) cv[q] = __ldg(reinterpret_cast<const uint4*>(p + (size_t)q * F_));
      }
    }
    if (elect && w == 0) TSTAMP(23);
    Q_STAGES(10, 18)
    if (elect && w == 0) TSTAMP(13);
    if (cw < 6) {
      float a[8];
#pragma unroll
      for (int i = 0; i < 8; i++) a[i] = 0.f;
#pragma unroll
      for (int q = 0; q < 10; q++) add8(a, cv[q]);
      col_reduce_store<3>(a, lane, true, g_cs + (j * 16 + mt) * 160 + 60 + 32 * (cw >> 1) + 16 * (cw & 1) + 2 * (lane & 7), tag);
    }
    Q_STAGES(18, 20)
    if (elect && w == 0) TSTAMP(25);

    float accA[64], accB[64];
    uint32_t h0[16], h1[16], h2[16], of[20];
    uint2* gq = g_qkv + (15 * j) * BLK + w * 4096 + (half0 + g) * 4 + t;

#define GU_STAGE0(ACC, G, FIRST)                                                       \
    {                                                                                  \
      mbar_wait(BAR(B_FULL + ((G) & 3)), ((G) >> 2) & 1);                              \
      wg_fence();                                                                      \
      const uint32_t a = xlo + (((G) - 20) % 10) * 1024, b = ringg + ((G) & 3) * 1024; \
      if (FIRST) wgmma_ss128_init(ACC, a, b); else wgmma_ss128(ACC, a, b);             \
      wgmma_ss128(ACC, a + 2, b + 128);                                                \
      wgmma_ss128(ACC, a + 4, b + 256);                                                \
      wgmma_ss128(ACC, a + 6, b + 384);                                                \
      wg_commit();                                                                     \
    }
#define GU_STAGE(ACC, G, FIRST)                                                        \
    {                                                                                  \
      GU_STAGE0(ACC, G, FIRST)                                                         \
      wg_wait<1>();                                                                    \
      if (elect) mbar_arrive(BAR(B_EMPTY + (((G) - 1) & 3)));                          \
    }

    mbar_wait(BAR(B_EPI), 0);
    const float2 s1 = ld_stats(&g_stats[R1], tag), s2 = ld_stats(&g_stats[R1 + 16], tag);
    GU_STAGE(accA, 20, true)
    fence_regs(accq);
    qkv_piece<0>(accq, s1, s2, cs_addr, gq); qkv_piece<1>(accq, s1, s2, cs_addr, gq);
    GU_STAGE(accA, 21, false)
    qkv_piece<2>(accq, s1, s2, cs_addr, gq); qkv_piece<3>(accq, s1, s2, cs_addr, gq);
    GU_STAGE(accA, 22, false)
    qkv_piece<4>(accq, s1, s2, cs_addr, gq);
    GU_STAGE(accA, 23, false)
    qkv_piece<5>(accq, s1, s2, cs_addr, gq); qkv_piece<6>(accq, s1, s2, cs_addr, gq);
    GU_STAGE(accA, 24, false)
    qkv_piece<7>(accq, s1, s2, cs_addr, gq);
    GU_STAGE(accA, 25, false)
    qkv_piece<8>(accq, s1, s2, cs_addr, gq); qkv_piece<9>(accq, s1, s2, cs_addr, gq);
    GU_STAGE(accA, 26, false)
    qkv_piece<10>(accq, s1, s2, cs_addr, gq);
    GU_STAGE(accA, 27, false)
    qkv_piece<11>(accq, s1, s2, cs_addr, gq); qkv_piece<12>(accq, s1, s2, cs_addr, gq);
    GU_STAGE(accA, 28, false)
    qkv_piece<13>(accq, s1, s2, cs_addr, gq);
    GU_STAGE(accA, 29, false)
    qkv_piece<14>(accq, s1, s2, cs_addr, gq);
    __syncwarp();
    if (lane == 0) mbar_arrive(BAR(B_QKVDONE));
    if (elect && w == 0) TSTAMP(26);

    const float3 e1 = make_float3(s1.x * -1.4426950408889634f, s1.y, rcpf(s1.x * s1.x));
    const float3 e2 = make_float3(s2.x * -1.4426950408889634f, s2.y, rcpf(s2.x * s2.x));
    GU_STAGE(accB, 30, true)
    fence_regs(accA);
    mbar_wait(BAR(B_GU), 0);
    GU_STAGE(accB, 31, false) gu_piece<0>(accA, e1, e2, cs_addr + 960, h0);
    GU_STAGE(accB, 32, false) gu_piece<1>(accA, e1, e2, cs_addr + 960, h0);
    GU_STAGE(accB, 33, false) gu_piece<2>(accA, e1, e2, cs_addr + 960, h0);
    GU_STAGE(accB, 34, false) gu_piece<3>(accA, e1, e2, cs_addr + 960, h0);
    GU_STAGE(accB, 35, false) gu_piece<4>(accA, e1, e2, cs_addr + 960, h0); gu_piece<5>(accA, e1, e2, cs_addr + 960, h0);
    GU_STAGE(accB, 36, false) gu_piece<6>(accA, e1, e2, cs_addr + 960, h0);
    GU_STAGE(accB, 37, false) gu_piece<7>(accA, e1, e2, cs_addr + 960, h0);
    AttnOps ao;
    GU_STAGE(accB, 38, false)
    mbar_wait(BAR(B_QKVRDY), 0);
    attn_load(ao, j, w, half0, g, t);
    GU_STAGE(accB, 39, false)
    wg_wait<0>();
    fence_regs(accB);
    if (elect) mbar_arrive(BAR(B_EMPTY + 3));
    if (elect && w == 0) TSTAMP(27);
    mbar_wait(BAR(B_QKVRDY), 0);
    attn_compute(ao, half0, g, t, of);
    if (elect && w == 0) TSTAMP(22);

    float accC[64];
    GU_STAGE0(accC, 40, true)
    gu_piece<0>(accB, e1, e2, cs_addr + 960 + 512, h1);
    GU_STAGE(accC, 41, false) gu_piece<1>(accB, e1, e2, cs_addr + 960 + 512, h1);
    GU_STAGE(accC, 42, false) gu_piece<2>(accB, e1, e2, cs_addr + 960 + 512, h1);
    GU_STAGE(accC, 43, false) gu_piece<3>(accB, e1, e2, cs_addr + 960 + 512, h1);
    GU_STAGE(accC, 44, false) gu_piece<4>(accB, e1, e2, cs_addr + 960 + 512, h1);
    GU_STAGE(accC, 45, false) gu_piece<5>(accB, e1, e2, cs_addr + 960 + 512, h1);
    GU_STAGE(accC, 46, false) gu_piece<6>(accB, e1, e2, cs_addr + 960 + 512, h1);
    GU_STAGE(accC, 47, false) gu_piece<7>(accB, e1, e2, cs_addr + 960 + 512, h1);
    GU_STAGE(accC, 48, false)
    GU_STAGE(accC, 49, false)
    if (elect && w == 0) TSTAMP(28);

    float acc0[32], acc1[32];
    const uint32_t cdesc = ((sb & 0x3FFFFu) >> 4) | (1u << 16);
    const int rho = j & 1, jp = j >> 1;
    asm volatile("barrier.cluster.wait.acquire.aligned;" ::: "memory");

    mbar_wait(BAR(B_CFULL + 0), 0);
    wg_fence();
    g2_h<true>(acc0, h0, cdesc);
    g2_h<false>(acc0, h1, cdesc + 512);
    wg_commit();
    wg_wait<1>();
    if (elect) mbar_arrive(BAR(B_EMPTY + 1));
    fence_regs(accC);
    gu_piece<0>(accC, e1, e2, cs_addr + 960 + 1024, h2); gu_piece<1>(accC, e1, e2, cs_addr + 960 + 1024, h2);
    gu_piece<2>(accC, e1, e2, cs_addr + 960 + 1024, h2); gu_piece<3>(accC, e1, e2, cs_addr + 960 + 1024, h2);
    wg_fence();
    g2_o(acc0, of, cdesc);
    wg_commit();
    gu_piece<4>(accC, e1, e2, cs_addr + 960 + 1024, h2); gu_piece<5>(accC, e1, e2, cs_addr + 960 + 1024, h2);
    gu_piece<6>(accC, e1, e2, cs_addr + 960 + 1024, h2); gu_piece<7>(accC, e1, e2, cs_addr + 960 + 1024, h2);
    wg_fence();
    g2_h<false>(acc0, h2, cdesc + 1024);
    wg_commit();
    if (elect && w == 0) TSTAMP(29);

#define G2_PART1(CUR, C)                                                                         \
      {                                                                                          \
        const int s_ = (C) < 6 ? (C) : (C) - 6;                                                  \
        const uint32_t bl = cdesc + s_ * (CSLOT >> 4);                                           \
        mbar_wait(BAR(B_CFULL + s_), (C) < 6 ? 0 : 1);                                           \
        wg_fence();                                                                              \
        g2_h<true>(CUR, h0, bl);                                                                 \
        g2_h<false>(CUR, h1, bl + 512);                                                          \
        wg_commit();                                                                             \
        wg_wait<1>();                                                                            \
        if ((C) - 1 < 4 && elect) mbar_arrive(BAR(B_CEMPTY + (C) - 1));                          \
      }
#define G2_PART2(CUR, C)                                                                         \
      {                                                                                          \
        const uint32_t bl = cdesc + ((C) < 6 ? (C) : (C) - 6) * (CSLOT >> 4);                    \
        wg_fence();                                                                              \
        g2_o(CUR, of, bl);                                                                       \
        g2_h<false>(CUR, h2, bl + 1024);                                                         \
        wg_commit();                                                                             \
      }

    const bool keeper = (w == rho);
    const uint32_t rbuf = sb + SM_RECV + tau * 16;
    const uint32_t peer_bar0 = mapa(bar0, rho ^ 1);
    const uint32_t peer_buf = mapa(rbuf, rho ^ 1);
    uint4* pp = g_part + ((size_t)(mt * 10) * 2 + rho) * 2048 + (keeper ? jp * 128 : jp * 512) + tau;
    const int RO = 2 * (half0 + g) + rho;
    const uint32_t* xp = reinterpret_cast<const uint32_t*>(prm.x) + (size_t)RO * (D_ / 2) + 8 * jp + t;
    uint32_t* op = reinterpret_cast<uint32_t*>(prm.out) + (size_t)RO * (D_ / 2) + 8 * jp + t;
    uint4 kp[4];
    Red red;
#define KEEP_ADD(K)                                                                              \
      {                                                                                          \
        mbar_wait(BAR(B_RFULL + (K)), 0);                                                        \
        pair_add_store(kp, rbuf + ((K) & 1) * 8192, pp + (K) * 4096, tag);                       \
        if ((K) + 2 <= 9) { __syncwarp(); if (lane == 0) mbar_arrive_remote(peer_bar0 + 8 * (B_REMPTY + (K) + 2)); } \
      }
#define KEEP_PACK(ACC) { kp[0] = pack8(ACC, 0); kp[1] = pack8(ACC, 1); kp[2] = pack8(ACC, 2); kp[3] = pack8(ACC, 3); }
#define SEND(ACC, K)                                                                             \
      {                                                                                          \
        if ((K) >= 2) mbar_wait(BAR(B_REMPTY + (K)), 0);                                         \
        pair_send(ACC, peer_buf + ((K) & 1) * 8192, peer_bar0 + 8 * (B_RFULL + (K)));            \
      }
#define G2_CHUNK(CUR, PREV, C)                                                                   \
      G2_PART1(CUR, C)                                                                           \
      fence_regs(PREV);                                                                          \
      if (keeper) {                                                                              \
        if ((C) >= 2) KEEP_ADD((C) - 2)                                                          \
        KEEP_PACK(PREV)                                                                          \
      } else {                                                                                   \
        SEND(PREV, (C) - 1)                                                                      \
      }                                                                                          \
      G2_PART2(CUR, C)                                                                           \
      if (!keeper) {                                                                             \
        if ((C) >= 5) red_finish(red, pp + ((C) - 5) * 4096, op + ((C) - 5) * 32, tag);          \
        if ((C) >= 4) red_load(red, pp + ((C) - 4) * 4096, xp + ((C) - 4) * 32);                 \
      }                                                                                          \
      if (elect && w == 0) TSTAMP(32 + 3 * ((C) - 1));
    G2_CHUNK(acc1, acc0, 1)
    G2_CHUNK(acc0, acc1, 2)
    G2_CHUNK(acc1, acc0, 3)
    G2_CHUNK(acc0, acc1, 4)
    G2_CHUNK(acc1, acc0, 5)
    G2_CHUNK(acc0, acc1, 6)
    G2_CHUNK(acc1, acc0, 7)
    G2_CHUNK(acc0, acc1, 8)
    G2_CHUNK(acc1, acc0, 9)
    if (keeper) KEEP_ADD(8)
    wg_wait<0>();
    fence_regs(acc1);
    if (elect && w == 0) TSTAMP(30);
    if (keeper) {
      KEEP_PACK(acc1)
      KEEP_ADD(9)
    } else {
      SEND(acc1, 9)
      Red r6, r7, r8, r9;
      red_load(r6, pp + 6 * 4096, xp + 6 * 32);
      red_load(r7, pp + 7 * 4096, xp + 7 * 32);
      red_finish(red, pp + 5 * 4096, op + 5 * 32, tag);
      red_load(r8, pp + 8 * 4096, xp + 8 * 32);
      red_finish(r6, pp + 6 * 4096, op + 6 * 32, tag);
      red_finish(r7, pp + 7 * 4096, op + 7 * 32, tag);
      red_load(r9, pp + 9 * 4096, xp + 9 * 32);
      red_finish(r8, pp + 8 * 4096, op + 8 * 32, tag);
      red_finish(r9, pp + 9 * 4096, op + 9 * 32, tag);
      if (elect) { TSTAMP(31); GSTAMP(63); atomicAdd(&g_flags[FL_DONE * 32], 1u); }
    }
  }
  __syncwarp();
  asm volatile("barrier.cluster.arrive.release.aligned;" ::: "memory");
  asm volatile("barrier.cluster.wait.acquire.aligned;" ::: "memory");
#undef BAR
}

typedef CUresult (*EncodeFn)(CUtensorMap*, CUtensorMapDataType, cuuint32_t, void*, const cuuint64_t*, const cuuint64_t*,
                             const cuuint32_t*, const cuuint32_t*, CUtensorMapInterleave, CUtensorMapSwizzle,
                             CUtensorMapL2promotion, CUtensorMapFloatOOBfill);

CUtensorMap make_map(EncodeFn enc, const void* base, int rank, const cuuint64_t* dims, const cuuint64_t* strides, const cuuint32_t* box) {
  CUtensorMap m;
  const cuuint32_t es[3] = {1, 1, 1};
  enc(&m, CU_TENSOR_MAP_DATA_TYPE_BFLOAT16, (cuuint32_t)rank, const_cast<void*>(base), dims, strides, box, es,
      CU_TENSOR_MAP_INTERLEAVE_NONE, CU_TENSOR_MAP_SWIZZLE_128B, CU_TENSOR_MAP_L2_PROMOTION_L2_128B,
      CU_TENSOR_MAP_FLOAT_OOB_FILL_NONE);
  return m;
}

}

extern "C" void kernel_launch(void* const* d_in, const int* in_sizes, int n_in, void* d_out, int out_size) {
  (void)in_sizes; (void)n_in; (void)out_size;
  static EncodeFn enc = nullptr;
  if (!enc) {
    void* fn = nullptr;
    cudaDriverEntryPointQueryResult q;
    cudaGetDriverEntryPoint("cuTensorMapEncodeTiled", &fn, cudaEnableDefault, &q);
    enc = (EncodeFn)fn;
    cudaFuncSetAttribute(fused_kernel, cudaFuncAttributeMaxDynamicSharedMemorySize, SM_TOTAL);
  }
  Params p;
  p.x = (const __nv_bfloat16*)d_in[0];
  p.wqkv = (const __nv_bfloat16*)d_in[1];
  p.wo = (const __nv_bfloat16*)d_in[2];
  p.w1 = (const __nv_bfloat16*)d_in[4];
  p.w3 = (const __nv_bfloat16*)d_in[5];
  p.w2 = (const __nv_bfloat16*)d_in[6];
  p.out = (__nv_bfloat16*)d_out;

  CUtensorMap tmX, tmQ3, tmQ1, tmW1, tmW3, tmW2, tmWo;
  { const cuuint64_t d[3] = {D_, S_ / 2, 2}, s[2] = {D_ * 4, D_ * 2}; const cuuint32_t b[3] = {64, 64, 2}; tmX = make_map(enc, p.x, 3, d, s, b); }
  { const cuuint64_t d[3] = {NQKV, D_, 3}, s[2] = {NQKV * 2, 128}; const cuuint32_t b[3] = {64, 32, 3}; tmQ3 = make_map(enc, p.wqkv, 3, d, s, b); }
  { const cuuint64_t d[2] = {NQKV, D_}, s[1] = {NQKV * 2}; const cuuint32_t b[2] = {64, 32}; tmQ1 = make_map(enc, p.wqkv, 2, d, s, b); }
  { const cuuint64_t d[2] = {F_, D_}, s[1] = {F_ * 2}; const cuuint32_t b[2] = {64, 64}; tmW1 = make_map(enc, p.w1, 2, d, s, b); tmW3 = make_map(enc, p.w3, 2, d, s, b); }
  { const cuuint64_t d[2] = {D_, F_}, s[1] = {D_ * 2}; const cuuint32_t b[2] = {64, 192}; tmW2 = make_map(enc, p.w2, 2, d, s, b); }
  { const cuuint64_t d[2] = {D_, D_}, s[1] = {D_ * 2}; const cuuint32_t b[2] = {64, 80}; tmWo = make_map(enc, p.wo, 2, d, s, b); }

  cudaLaunchConfig_t cfg = {};
  cfg.gridDim = dim3(128);
  cfg.blockDim = dim3(NTHREADS);
  cfg.dynamicSmemBytes = SM_TOTAL;
  cfg.stream = cudaStreamPerThread;
  cudaLaunchAttribute at[1];
  at[0].id = cudaLaunchAttributeClusterDimension;
  at[0].val.clusterDim.x = 2; at[0].val.clusterDim.y = 1; at[0].val.clusterDim.z = 1;
  cfg.attrs = at; cfg.numAttrs = 1;
  cudaLaunchKernelEx(&cfg, fused_kernel, tmX, tmQ3, tmQ1, tmW1, tmW3, tmW2, tmWo, p);
}
```

```cpp
#include <cuda_runtime.h>
#include <cuda_bf16.h>
#include <cuda.h>
#include <stdint.h>

namespace {

constexpr int S_ = 2048, D_ = 640, F_ = 1536, NQKV = 1920;
constexpr int NTHREADS = 384;

constexpr int SM_X    = 0;
constexpr int SM_RING = 163840;
constexpr int SLOT    = 16384;
constexpr int QBYTES  = 15360;
constexpr int CSLOT   = 34816;
constexpr int SM_RECV = 196608;
constexpr int SM_LAST = 174080;
constexpr int SM_CSA  = 229376;
constexpr int SM_CSB  = SM_CSA + 960;
constexpr int SM_CSC  = SM_CSB + 1024;
constexpr int SM_BAR  = 231872;
constexpr int SM_TOTAL = 232448;
constexpr int B_XFULL = 0, B_FULL = 10, B_EMPTY = 14, B_CFULL = 18, B_CEMPTY = 23, B_EPI = 28, B_GU = 29, B_PUB = 32,
              B_RFULL = 36, B_CSFREE = 45, B_REMPTY = 46, B_INIT = 47, B_EMPTYQ = 57, B_XFREE = 61, B_PUBQ = 62, B_COUNT = 63;

constexpr uint32_t SPIN_LIMIT = 1u << 17;
constexpr uint32_t DESC_HI   = 0x40000040u;
constexpr uint32_t DESC_HI32 = 0xC0000010u;

__device__ uint4  g_halo[8 * 2 * 64 * 5 * 32];
__device__ unsigned g_init[16 * 8];
__device__ float2 g_stats[S_];
__device__ float  g_cs[8 * 4 * 512];
__device__ unsigned g_done[32];
#define TSTAMP(id) do {} while (0)
#define GSTAMP(id) do {} while (0)
#define TVALUE(id, v) do { (void)(v); } while (0)

struct Params {
  const __nv_bfloat16* x;
  const __nv_bfloat16* wqkv;
  const __nv_bfloat16* w1;
  const __nv_bfloat16* w3;
  __nv_bfloat16* out;
  uint32_t zero;
};

__device__ __forceinline__ uint32_t smem_u32(const void* p) { return (uint32_t)__cvta_generic_to_shared(p); }
__device__ __forceinline__ bool elect_one() {
  uint32_t p;
  asm volatile("{\n.reg .pred P;\nelect.sync _|P, 0xffffffff;\nselp.u32 %0, 1, 0, P;\n}" : "=r"(p));
  return p != 0;
}
__device__ __forceinline__ void mbar_init(uint32_t bar, uint32_t cnt) {
  asm volatile("mbarrier.init.shared::cta.b64 [%0], %1;" ::"r"(bar), "r"(cnt) : "memory");
}
__device__ __forceinline__ void mbar_expect_tx(uint32_t bar, uint32_t bytes) {
  asm volatile("mbarrier.arrive.expect_tx.shared::cta.b64 _, [%0], %1;" ::"r"(bar), "r"(bytes) : "memory");
}
__device__ __forceinline__ void mbar_arrive(uint32_t bar) {
  asm volatile("mbarrier.arrive.shared::cta.b64 _, [%0];" ::"r"(bar) : "memory");
}
__device__ __forceinline__ bool mbar_try(uint32_t bar, uint32_t parity) {
  uint32_t ok;
  asm volatile("{\n.reg .pred p;\nmbarrier.try_wait.parity.shared::cta.b64 p, [%1], %2;\nselp.u32 %0, 1, 0, p;\n}"
               : "=r"(ok) : "r"(bar), "r"(parity) : "memory");
  return ok != 0;
}
__device__ __forceinline__ void mbar_wait(uint32_t bar, uint32_t parity) {
  uint32_t it = 0;
#pragma unroll 1
  while (!mbar_try(bar, parity)) { if (++it > SPIN_LIMIT) break; }
}
__device__ __forceinline__ bool mbar_test(uint32_t bar, uint32_t parity) {
  uint32_t ok;
  asm volatile("{\n.reg .pred p;\nmbarrier.test_wait.parity.shared::cta.b64 p, [%1], %2;\nselp.u32 %0, 1, 0, p;\n}"
               : "=r"(ok) : "r"(bar), "r"(parity) : "memory");
  return ok != 0;
}
__device__ __forceinline__ void tma2d(uint32_t dst, const CUtensorMap* m, int c0, int c1, uint32_t bar) {
  asm volatile("cp.async.bulk.tensor.2d.shared::cluster.global.mbarrier::complete_tx::bytes [%0], [%1, {%3, %4}], [%2];"
               ::"r"(dst), "l"(m), "r"(bar), "r"(c0), "r"(c1) : "memory");
}
__device__ __forceinline__ void tma3d(uint32_t dst, const CUtensorMap* m, int c0, int c1, int c2, uint32_t bar) {
  asm volatile("cp.async.bulk.tensor.3d.shared::cluster.global.mbarrier::complete_tx::bytes [%0], [%1, {%3, %4, %5}], [%2];"
               ::"r"(dst), "l"(m), "r"(bar), "r"(c0), "r"(c1), "r"(c2) : "memory");
}
__device__ __forceinline__ void tma3d_mc(uint32_t dst, const CUtensorMap* m, int c0, int c1, int c2, uint32_t bar) {
  asm volatile("cp.async.bulk.tensor.3d.shared::cluster.global.mbarrier::complete_tx::bytes.multicast::cluster [%0], [%1, {%3, %4, %5}], [%2], %6;"
               ::"r"(dst), "l"(m), "r"(bar), "r"(c0), "r"(c1), "r"(c2), "h"((uint16_t)3) : "memory");
}
__device__ __forceinline__ void tma_store3d(const CUtensorMap* m, uint32_t src, int c0, int c1, int c2) {
  asm volatile("cp.async.bulk.tensor.3d.global.shared::cta.tile.bulk_group [%0, {%2, %3, %4}], [%1];"
               ::"l"(m), "r"(src), "r"(c0), "r"(c1), "r"(c2) : "memory");
}
__device__ __forceinline__ void tma_add3d(const CUtensorMap* m, uint32_t src, int c0, int c1, int c2) {
  asm volatile("cp.reduce.async.bulk.tensor.3d.global.shared::cta.add.tile.bulk_group [%0, {%2, %3, %4}], [%1];"
               ::"l"(m), "r"(src), "r"(c0), "r"(c1), "r"(c2) : "memory");
}
__device__ __forceinline__ void bulk_to_peer(uint32_t dst_cluster, uint32_t src, uint32_t bytes, uint32_t bar_cluster) {
  asm volatile("cp.async.bulk.shared::cluster.shared::cta.mbarrier::complete_tx::bytes [%0], [%1], %2, [%3];"
               ::"r"(dst_cluster), "r"(src), "r"(bytes), "r"(bar_cluster) : "memory");
}
__device__ __forceinline__ void bulk_commit() { asm volatile("cp.async.bulk.commit_group;" ::: "memory"); }
template <int N> __device__ __forceinline__ void bulk_wait_read() { asm volatile("cp.async.bulk.wait_group.read %0;" ::"n"(N) : "memory"); }
__device__ __forceinline__ void fence_async() { asm volatile("fence.proxy.async;" ::: "memory"); }
__device__ __forceinline__ void fence_async_smem() { asm volatile("fence.proxy.async.shared::cta;" ::: "memory"); }
__device__ __forceinline__ void stsm4(uint32_t addr, const uint4 v) {
  asm volatile("stmatrix.sync.aligned.m8n8.x4.shared.b16 [%0], {%1, %2, %3, %4};" ::"r"(addr), "r"(v.x), "r"(v.y), "r"(v.z), "r"(v.w) : "memory");
}
__device__ __forceinline__ void prefetch_tmap(const CUtensorMap* m) {
  asm volatile("prefetch.tensormap [%0];" ::"l"(m) : "memory");
}
__device__ __forceinline__ void wg_fence() { asm volatile("wgmma.fence.sync.aligned;" ::: "memory"); }
__device__ __forceinline__ void wg_commit() { asm volatile("wgmma.commit_group.sync.aligned;" ::: "memory"); }
template <int N> __device__ __forceinline__ void wg_wait() { asm volatile("wgmma.wait_group.sync.aligned %0;" ::"n"(N) : "memory"); }
template <int N> __device__ __forceinline__ void fence_regs(float (&a)[N]) {
#pragma unroll
  for (int i = 0; i < N; i++) asm volatile("" : "+f"(a[i]) :: "memory");
}
__device__ __forceinline__ uint32_t pack_bf16(float lo, float hi) {
  uint32_t r;
  asm("cvt.rn.bf16x2.f32 %0, %1, %2;" : "=r"(r) : "f"(hi), "f"(lo));
  return r;
}
__device__ __forceinline__ float bf_lo(uint32_t w) { return __uint_as_float(w << 16); }
__device__ __forceinline__ float bf_hi(uint32_t w) { return __uint_as_float(w & 0xffff0000u); }
__device__ __forceinline__ float2 lds64f(uint32_t addr) {
  float2 v;
  asm volatile("ld.shared.v2.f32 {%0, %1}, [%2];" : "=f"(v.x), "=f"(v.y) : "r"(addr));
  return v;
}
__device__ __forceinline__ uint32_t lds32(uint32_t addr) {
  uint32_t v;
  asm volatile("ld.shared.b32 %0, [%1];" : "=r"(v) : "r"(addr) : "memory");
  return v;
}
__device__ __forceinline__ uint4 lds128(uint32_t addr) {
  uint4 v;
  asm volatile("ld.shared.v4.b32 {%0, %1, %2, %3}, [%4];" : "=r"(v.x), "=r"(v.y), "=r"(v.z), "=r"(v.w) : "r"(addr) : "memory");
  return v;
}
__device__ __forceinline__ void sts128(uint32_t addr, uint4 v) {
  asm volatile("st.shared.v4.b32 [%0], {%1, %2, %3, %4};" ::"r"(addr), "r"(v.x), "r"(v.y), "r"(v.z), "r"(v.w) : "memory");
}
__device__ __forceinline__ float ex2f(float x) { float y; asm("ex2.approx.ftz.f32 %0, %1;" : "=f"(y) : "f"(x)); return y; }
__device__ __forceinline__ float rcpf(float x) { float y; asm("rcp.approx.ftz.f32 %0, %1;" : "=f"(y) : "f"(x)); return y; }
__device__ __forceinline__ void mma16816(float (&c)[4], uint32_t a0, uint32_t a1, uint32_t a2, uint32_t a3, uint32_t b0, uint32_t b1) {
  asm volatile("mma.sync.aligned.m16n8k16.row.col.f32.bf16.bf16.f32 {%0,%1,%2,%3}, {%4,%5,%6,%7}, {%8,%9}, {%0,%1,%2,%3};"
               : "+f"(c[0]), "+f"(c[1]), "+f"(c[2]), "+f"(c[3]) : "r"(a0), "r"(a1), "r"(a2), "r"(a3), "r"(b0), "r"(b1));
}
__device__ __forceinline__ void mma1688(float (&c)[4], uint32_t a0, uint32_t a1, uint32_t b0) {
  asm volatile("mma.sync.aligned.m16n8k8.row.col.f32.bf16.bf16.f32 {%0,%1,%2,%3}, {%4,%5}, {%6}, {%0,%1,%2,%3};"
               : "+f"(c[0]), "+f"(c[1]), "+f"(c[2]), "+f"(c[3]) : "r"(a0), "r"(a1), "r"(b0));
}
__device__ __forceinline__ uint32_t movm(uint32_t a) {
  uint32_t d;
  asm volatile("movmatrix.sync.aligned.m8n8.trans.b16 %0, %1;" : "=r"(d) : "r"(a));
  return d;
}
__device__ __forceinline__ uint32_t mapa(uint32_t addr, uint32_t rank) {
  uint32_t r;
  asm("mapa.shared::cluster.u32 %0, %1, %2;" : "=r"(r) : "r"(addr), "r"(rank));
  return r;
}
__device__ __forceinline__ void mbar_arrive_remote(uint32_t cluster_addr) {
  asm volatile("mbarrier.arrive.shared::cluster.b64 _, [%0];" ::"r"(cluster_addr) : "memory");
}
__device__ __forceinline__ void st_async(uint32_t cluster_addr, uint4 v, uint32_t cluster_bar) {
  asm volatile("st.async.weak.shared::cluster.mbarrier::complete_tx::bytes.v4.b32 [%0], {%1, %2, %3, %4}, [%5];"
               ::"r"(cluster_addr), "r"(v.x), "r"(v.y), "r"(v.z), "r"(v.w), "r"(cluster_bar) : "memory");
}
__device__ __forceinline__ void st_tagged(void* p, uint4 v) {
  asm volatile("{\n.reg .b128 r;\nmov.b128 r, {%1, %2};\nst.relaxed.gpu.global.b128 [%0], r;\n}"
               ::"l"(p), "l"(((uint64_t)v.y << 32) | v.x), "l"(((uint64_t)v.w << 32) | v.z) : "memory");
}
__device__ __forceinline__ uint4 ld_tagged(const void* p) {
  uint64_t a, b;
  asm volatile("{\n.reg .b128 r;\nld.relaxed.gpu.global.b128 r, [%2];\nmov.b128 {%0, %1}, r;\n}" : "=l"(a), "=l"(b) : "l"(p) : "memory");
  return make_uint4((uint32_t)a, (uint32_t)(a >> 32), (uint32_t)b, (uint32_t)(b >> 32));
}
__device__ __forceinline__ void st_tagged64(void* p, uint32_t x, uint32_t y) {
  asm volatile("st.relaxed.gpu.global.b64 [%0], %1;" ::"l"(p), "l"(((uint64_t)y << 32) | x) : "memory");
}
__device__ __forceinline__ void st_tagged32(void* p, uint32_t x) {
  asm volatile("st.relaxed.gpu.global.b32 [%0], %1;" ::"l"(p), "r"(x) : "memory");
}
__device__ __forceinline__ uint32_t set_tag(uint32_t w, uint32_t tag) { return (w & 0xfffffffeu) | tag; }
__device__ __forceinline__ uint32_t launch_tag() {
  unsigned v;
  asm volatile("ld.relaxed.gpu.global.u32 %0, [%1];" : "=r"(v) : "l"(&g_done[0]) : "memory");
  return ((v >> 7) + 1) & 1u;
}

__device__ __forceinline__ void wgmma_rs64_sc(float (&d)[32], uint32_t a0, uint32_t a1, uint32_t a2, uint32_t a3, uint32_t blo, uint32_t sc) {
  asm volatile("{\n.reg .pred p;\n.reg .b64 db;\n"
    "setp.ne.b32 p, %38, 0;\n"
    "mov.b64 db, {%36, %37};\n"
    "wgmma.mma_async.sync.aligned.m64n64k16.f32.bf16.bf16 {%0, %1, %2, %3, %4, %5, %6, %7, %8, %9, %10, %11, %12, %13, %14, %15, %16, %17, %18, %19, %20, %21, %22, %23, %24, %25, %26, %27, %28, %29, %30, %31}, {%32,%33,%34,%35}, db, p, 1, 1, 1;\n}\n"
    :
        "+f"(d[0]), "+f"(d[1]), "+f"(d[2]), "+f"(d[3]), "+f"(d[4]), "+f"(d[5]), "+f"(d[6]), "+f"(d[7]),
        "+f"(d[8]), "+f"(d[9]), "+f"(d[10]), "+f"(d[11]), "+f"(d[12]), "+f"(d[13]), "+f"(d[14]), "+f"(d[15]),
        "+f"(d[16]), "+f"(d[17]), "+f"(d[18]), "+f"(d[19]), "+f"(d[20]), "+f"(d[21]), "+f"(d[22]), "+f"(d[23]),
        "+f"(d[24]), "+f"(d[25]), "+f"(d[26]), "+f"(d[27]), "+f"(d[28]), "+f"(d[29]), "+f"(d[30]), "+f"(d[31])
    : "r"(a0), "r"(a1), "r"(a2), "r"(a3), "r"(blo), "n"(DESC_HI), "r"(sc));
}
__device__ __forceinline__ void wgmma_ss192(float (&d)[96], uint32_t alo, uint32_t blo) {
  asm volatile("{\n.reg .pred p;\n.reg .b64 da, db;\n"
    "setp.eq.b32 p, 0, 0;\n"
    "mov.b64 da, {%96, %98};\nmov.b64 db, {%97, %99};\n"
    "wgmma.mma_async.sync.aligned.m64n192k16.f32.bf16.bf16 {%0, %1, %2, %3, %4, %5, %6, %7, %8, %9, %10, %11, %12, %13, %14, %15, %16, %17, %18, %19, %20, %21, %22, %23, %24, %25, %26, %27, %28, %29, %30, %31, %32, %33, %34, %35, %36, %37, %38, %39, %40, %41, %42, %43, %44, %45, %46, %47, %48, %49, %50, %51, %52, %53, %54, %55, %56, %57, %58, %59, %60, %61, %62, %63, %64, %65, %66, %67, %68, %69, %70, %71, %72, %73, %74, %75, %76, %77, %78, %79, %80, %81, %82, %83, %84, %85, %86, %87, %88, %89, %90, %91, %92, %93, %94, %95}, da, db, p, 1, 1, 0, 1;\n}\n"
    :
        "+f"(d[0]), "+f"(d[1]), "+f"(d[2]), "+f"(d[3]), "+f"(d[4]), "+f"(d[5]), "+f"(d[6]), "+f"(d[7]),
        "+f"(d[8]), "+f"(d[9]), "+f"(d[10]), "+f"(d[11]), "+f"(d[12]), "+f"(d[13]), "+f"(d[14]), "+f"(d[15]),
        "+f"(d[16]), "+f"(d[17]), "+f"(d[18]), "+f"(d[19]), "+f"(d[20]), "+f"(d[21]), "+f"(d[22]), "+f"(d[23]),
        "+f"(d[24]), "+f"(d[25]), "+f"(d[26]), "+f"(d[27]), "+f"(d[28]), "+f"(d[29]), "+f"(d[30]), "+f"(d[31]),
        "+f"(d[32]), "+f"(d[33]), "+f"(d[34]), "+f"(d[35]), "+f"(d[36]), "+f"(d[37]), "+f"(d[38]), "+f"(d[39]),
        "+f"(d[40]), "+f"(d[41]), "+f"(d[42]), "+f"(d[43]), "+f"(d[44]), "+f"(d[45]), "+f"(d[46]), "+f"(d[47]),
        "+f"(d[48]), "+f"(d[49]), "+f"(d[50]), "+f"(d[51]), "+f"(d[52]), "+f"(d[53]), "+f"(d[54]), "+f"(d[55]),
        "+f"(d[56]), "+f"(d[57]), "+f"(d[58]), "+f"(d[59]), "+f"(d[60]), "+f"(d[61]), "+f"(d[62]), "+f"(d[63]),
        "+f"(d[64]), "+f"(d[65]), "+f"(d[66]), "+f"(d[67]), "+f"(d[68]), "+f"(d[69]), "+f"(d[70]), "+f"(d[71]),
        "+f"(d[72]), "+f"(d[73]), "+f"(d[74]), "+f"(d[75]), "+f"(d[76]), "+f"(d[77]), "+f"(d[78]), "+f"(d[79]),
        "+f"(d[80]), "+f"(d[81]), "+f"(d[82]), "+f"(d[83]), "+f"(d[84]), "+f"(d[85]), "+f"(d[86]), "+f"(d[87]),
        "+f"(d[88]), "+f"(d[89]), "+f"(d[90]), "+f"(d[91]), "+f"(d[92]), "+f"(d[93]), "+f"(d[94]), "+f"(d[95])
    : "r"(alo), "r"(blo), "n"(DESC_HI), "n"(DESC_HI));
}
__device__ __forceinline__ void wgmma_ss48r(float (&d)[24], uint32_t alo, uint32_t blo) {
  asm volatile("{\n.reg .pred p;\n.reg .b64 da, db;\n"
    "setp.eq.b32 p, 0, 0;\n"
    "mov.b64 da, {%24, %26};\nmov.b64 db, {%25, %27};\n"
    "wgmma.mma_async.sync.aligned.m64n48k16.f32.bf16.bf16 {%0, %1, %2, %3, %4, %5, %6, %7, %8, %9, %10, %11, %12, %13, %14, %15, %16, %17, %18, %19, %20, %21, %22, %23}, da, db, p, 1, 1, 0, 1;\n}\n"
    :
        "+f"(d[0]), "+f"(d[1]), "+f"(d[2]), "+f"(d[3]), "+f"(d[4]), "+f"(d[5]), "+f"(d[6]), "+f"(d[7]),
        "+f"(d[8]), "+f"(d[9]), "+f"(d[10]), "+f"(d[11]), "+f"(d[12]), "+f"(d[13]), "+f"(d[14]), "+f"(d[15]),
        "+f"(d[16]), "+f"(d[17]), "+f"(d[18]), "+f"(d[19]), "+f"(d[20]), "+f"(d[21]), "+f"(d[22]), "+f"(d[23])
    : "r"(alo), "r"(blo), "n"(DESC_HI), "n"(DESC_HI32));
}
__device__ __forceinline__ void wgmma_ss128_init(float (&d)[64], uint32_t alo, uint32_t blo) {
  asm volatile("{\n.reg .pred p;\n.reg .b64 da, db;\n"
    "setp.ne.b32 p, 0, 0;\n"
    "mov.b64 da, {%64, %66};\nmov.b64 db, {%65, %66};\n"
    "wgmma.mma_async.sync.aligned.m64n128k16.f32.bf16.bf16 {%0, %1, %2, %3, %4, %5, %6, %7, %8, %9, %10, %11, %12, %13, %14, %15, %16, %17, %18, %19, %20, %21, %22, %23, %24, %25, %26, %27, %28, %29, %30, %31, %32, %33, %34, %35, %36, %37, %38, %39, %40, %41, %42, %43, %44, %45, %46, %47, %48, %49, %50, %51, %52, %53, %54, %55, %56, %57, %58, %59, %60, %61, %62, %63}, da, db, p, 1, 1, 0, 1;\n}\n"
    :
        "=f"(d[0]), "=f"(d[1]), "=f"(d[2]), "=f"(d[3]), "=f"(d[4]), "=f"(d[5]), "=f"(d[6]), "=f"(d[7]),
        "=f"(d[8]), "=f"(d[9]), "=f"(d[10]), "=f"(d[11]), "=f"(d[12]), "=f"(d[13]), "=f"(d[14]), "=f"(d[15]),
        "=f"(d[16]), "=f"(d[17]), "=f"(d[18]), "=f"(d[19]), "=f"(d[20]), "=f"(d[21]), "=f"(d[22]), "=f"(d[23]),
        "=f"(d[24]), "=f"(d[25]), "=f"(d[26]), "=f"(d[27]), "=f"(d[28]), "=f"(d[29]), "=f"(d[30]), "=f"(d[31]),
        "=f"(d[32]), "=f"(d[33]), "=f"(d[34]), "=f"(d[35]), "=f"(d[36]), "=f"(d[37]), "=f"(d[38]), "=f"(d[39]),
        "=f"(d[40]), "=f"(d[41]), "=f"(d[42]), "=f"(d[43]), "=f"(d[44]), "=f"(d[45]), "=f"(d[46]), "=f"(d[47]),
        "=f"(d[48]), "=f"(d[49]), "=f"(d[50]), "=f"(d[51]), "=f"(d[52]), "=f"(d[53]), "=f"(d[54]), "=f"(d[55]),
        "=f"(d[56]), "=f"(d[57]), "=f"(d[58]), "=f"(d[59]), "=f"(d[60]), "=f"(d[61]), "=f"(d[62]), "=f"(d[63])
    : "r"(alo), "r"(blo), "n"(DESC_HI));
}
__device__ __forceinline__ void wgmma_ss128_sc(float (&d)[64], uint32_t alo, uint32_t blo, uint32_t sc) {
  asm volatile("{\n.reg .pred p;\n.reg .b64 da, db;\n"
    "setp.ne.b32 p, %67, 0;\n"
    "mov.b64 da, {%64, %66};\nmov.b64 db, {%65, %66};\n"
    "wgmma.mma_async.sync.aligned.m64n128k16.f32.bf16.bf16 {%0, %1, %2, %3, %4, %5, %6, %7, %8, %9, %10, %11, %12, %13, %14, %15, %16, %17, %18, %19, %20, %21, %22, %23, %24, %25, %26, %27, %28, %29, %30, %31, %32, %33, %34, %35, %36, %37, %38, %39, %40, %41, %42, %43, %44, %45, %46, %47, %48, %49, %50, %51, %52, %53, %54, %55, %56, %57, %58, %59, %60, %61, %62, %63}, da, db, p, 1, 1, 0, 1;\n}\n"
    :
        "+f"(d[0]), "+f"(d[1]), "+f"(d[2]), "+f"(d[3]), "+f"(d[4]), "+f"(d[5]), "+f"(d[6]), "+f"(d[7]),
        "+f"(d[8]), "+f"(d[9]), "+f"(d[10]), "+f"(d[11]), "+f"(d[12]), "+f"(d[13]), "+f"(d[14]), "+f"(d[15]),
        "+f"(d[16]), "+f"(d[17]), "+f"(d[18]), "+f"(d[19]), "+f"(d[20]), "+f"(d[21]), "+f"(d[22]), "+f"(d[23]),
        "+f"(d[24]), "+f"(d[25]), "+f"(d[26]), "+f"(d[27]), "+f"(d[28]), "+f"(d[29]), "+f"(d[30]), "+f"(d[31]),
        "+f"(d[32]), "+f"(d[33]), "+f"(d[34]), "+f"(d[35]), "+f"(d[36]), "+f"(d[37]), "+f"(d[38]), "+f"(d[39]),
        "+f"(d[40]), "+f"(d[41]), "+f"(d[42]), "+f"(d[43]), "+f"(d[44]), "+f"(d[45]), "+f"(d[46]), "+f"(d[47]),
        "+f"(d[48]), "+f"(d[49]), "+f"(d[50]), "+f"(d[51]), "+f"(d[52]), "+f"(d[53]), "+f"(d[54]), "+f"(d[55]),
        "+f"(d[56]), "+f"(d[57]), "+f"(d[58]), "+f"(d[59]), "+f"(d[60]), "+f"(d[61]), "+f"(d[62]), "+f"(d[63])
    : "r"(alo), "r"(blo), "n"(DESC_HI), "r"(sc));
}
__device__ __forceinline__ void wgmma_ss128(float (&d)[64], uint32_t alo, uint32_t blo) {
  asm volatile("{\n.reg .pred p;\n.reg .b64 da, db;\n"
    "setp.eq.b32 p, 0, 0;\n"
    "mov.b64 da, {%64, %66};\nmov.b64 db, {%65, %67};\n"
    "wgmma.mma_async.sync.aligned.m64n128k16.f32.bf16.bf16 {%0, %1, %2, %3, %4, %5, %6, %7, %8, %9, %10, %11, %12, %13, %14, %15, %16, %17, %18, %19, %20, %21, %22, %23, %24, %25, %26, %27, %28, %29, %30, %31, %32, %33, %34, %35, %36, %37, %38, %39, %40, %41, %42, %43, %44, %45, %46, %47, %48, %49, %50, %51, %52, %53, %54, %55, %56, %57, %58, %59, %60, %61, %62, %63}, da, db, p, 1, 1, 0, 1;\n}\n"
    :
        "+f"(d[0]), "+f"(d[1]), "+f"(d[2]), "+f"(d[3]), "+f"(d[4]), "+f"(d[5]), "+f"(d[6]), "+f"(d[7]),
        "+f"(d[8]), "+f"(d[9]), "+f"(d[10]), "+f"(d[11]), "+f"(d[12]), "+f"(d[13]), "+f"(d[14]), "+f"(d[15]),
        "+f"(d[16]), "+f"(d[17]), "+f"(d[18]), "+f"(d[19]), "+f"(d[20]), "+f"(d[21]), "+f"(d[22]), "+f"(d[23]),
        "+f"(d[24]), "+f"(d[25]), "+f"(d[26]), "+f"(d[27]), "+f"(d[28]), "+f"(d[29]), "+f"(d[30]), "+f"(d[31]),
        "+f"(d[32]), "+f"(d[33]), "+f"(d[34]), "+f"(d[35]), "+f"(d[36]), "+f"(d[37]), "+f"(d[38]), "+f"(d[39]),
        "+f"(d[40]), "+f"(d[41]), "+f"(d[42]), "+f"(d[43]), "+f"(d[44]), "+f"(d[45]), "+f"(d[46]), "+f"(d[47]),
        "+f"(d[48]), "+f"(d[49]), "+f"(d[50]), "+f"(d[51]), "+f"(d[52]), "+f"(d[53]), "+f"(d[54]), "+f"(d[55]),
        "+f"(d[56]), "+f"(d[57]), "+f"(d[58]), "+f"(d[59]), "+f"(d[60]), "+f"(d[61]), "+f"(d[62]), "+f"(d[63])
    : "r"(alo), "r"(blo), "n"(DESC_HI), "n"(DESC_HI));
}
__device__ __forceinline__ void wgmma_rs64_init(float (&d)[32], uint32_t a0, uint32_t a1, uint32_t a2, uint32_t a3, uint32_t blo) {
  asm volatile("{\n.reg .pred p;\n.reg .b64 db;\n"
    "setp.ne.b32 p, 0, 0;\n"
    "mov.b64 db, {%36, %37};\n"
    "wgmma.mma_async.sync.aligned.m64n64k16.f32.bf16.bf16 {%0, %1, %2, %3, %4, %5, %6, %7, %8, %9, %10, %11, %12, %13, %14, %15, %16, %17, %18, %19, %20, %21, %22, %23, %24, %25, %26, %27, %28, %29, %30, %31}, {%32,%33,%34,%35}, db, p, 1, 1, 1;\n}\n"
    :
        "=f"(d[0]), "=f"(d[1]), "=f"(d[2]), "=f"(d[3]), "=f"(d[4]), "=f"(d[5]), "=f"(d[6]), "=f"(d[7]),
        "=f"(d[8]), "=f"(d[9]), "=f"(d[10]), "=f"(d[11]), "=f"(d[12]), "=f"(d[13]), "=f"(d[14]), "=f"(d[15]),
        "=f"(d[16]), "=f"(d[17]), "=f"(d[18]), "=f"(d[19]), "=f"(d[20]), "=f"(d[21]), "=f"(d[22]), "=f"(d[23]),
        "=f"(d[24]), "=f"(d[25]), "=f"(d[26]), "=f"(d[27]), "=f"(d[28]), "=f"(d[29]), "=f"(d[30]), "=f"(d[31])
    : "r"(a0), "r"(a1), "r"(a2), "r"(a3), "r"(blo), "n"(DESC_HI));
}
__device__ __forceinline__ void wgmma_rs64(float (&d)[32], uint32_t a0, uint32_t a1, uint32_t a2, uint32_t a3, uint32_t blo) {
  asm volatile("{\n.reg .pred p;\n.reg .b64 db;\n"
    "setp.eq.b32 p, 0, 0;\n"
    "mov.b64 db, {%36, %37};\n"
    "wgmma.mma_async.sync.aligned.m64n64k16.f32.bf16.bf16 {%0, %1, %2, %3, %4, %5, %6, %7, %8, %9, %10, %11, %12, %13, %14, %15, %16, %17, %18, %19, %20, %21, %22, %23, %24, %25, %26, %27, %28, %29, %30, %31}, {%32,%33,%34,%35}, db, p, 1, 1, 1;\n}\n"
    :
        "+f"(d[0]), "+f"(d[1]), "+f"(d[2]), "+f"(d[3]), "+f"(d[4]), "+f"(d[5]), "+f"(d[6]), "+f"(d[7]),
        "+f"(d[8]), "+f"(d[9]), "+f"(d[10]), "+f"(d[11]), "+f"(d[12]), "+f"(d[13]), "+f"(d[14]), "+f"(d[15]),
        "+f"(d[16]), "+f"(d[17]), "+f"(d[18]), "+f"(d[19]), "+f"(d[20]), "+f"(d[21]), "+f"(d[22]), "+f"(d[23]),
        "+f"(d[24]), "+f"(d[25]), "+f"(d[26]), "+f"(d[27]), "+f"(d[28]), "+f"(d[29]), "+f"(d[30]), "+f"(d[31])
    : "r"(a0), "r"(a1), "r"(a2), "r"(a3), "r"(blo), "n"(DESC_HI));
}

__device__ __forceinline__ float pin(float x, uint32_t zero) {
  uint32_t c;
  asm volatile("mov.u32 %0, %%clock;" : "=r"(c) :: "memory");
  return __uint_as_float(__float_as_uint(x) ^ (c & zero));
}
struct CS { float2 a, b; };
template <int S, int B>
__device__ __forceinline__ CS qkv_cs(uint32_t cs_addr) {
  constexpr int COL = (B < 4) ? 64 * S + 16 * B : 192 + 16 * S;
  CS c; c.a = lds64f(cs_addr + COL * 4); c.b = lds64f(cs_addr + (COL + 8) * 4);
  return c;
}
template <int S, int B>
__device__ __forceinline__ void qkv_piece(const float (&am)[96], const float (&ar)[24], float2 s1, float2 s2, const CS c,
                                          uint2& w1, uint2& w2) {
  float a[8];
#pragma unroll
  for (int i = 0; i < 8; i++) a[i] = (B < 4) ? am[(B < 4 ? 32 * S + 8 * B : 0) + i] : ar[(B < 4 ? 0 : 8 * S) + i];
  w1.x = pack_bf16(s1.x * fmaf(s1.y, c.a.x, a[0]), s1.x * fmaf(s1.y, c.a.y, a[1]));
  w2.x = pack_bf16(s2.x * fmaf(s2.y, c.a.x, a[2]), s2.x * fmaf(s2.y, c.a.y, a[3]));
  w1.y = pack_bf16(s1.x * fmaf(s1.y, c.b.x, a[4]), s1.x * fmaf(s1.y, c.b.y, a[5]));
  w2.y = pack_bf16(s2.x * fmaf(s2.y, c.b.x, a[6]), s2.x * fmaf(s2.y, c.b.y, a[7]));
}
__device__ __forceinline__ float swiglu(float ag, float au, float cg, float cu, const float3 s) {
  const float g = fmaf(s.y, cg, ag), u = fmaf(s.y, cu, au);
  const float e = ex2f(g * s.x);
  return (g * u) * rcpf(fmaf(e, s.z, s.z));
}
template <int NB>
__device__ __forceinline__ CS gu_cs(uint32_t cs_addr) {
  CS c; c.a = lds64f(cs_addr + (8 * NB) * 4); c.b = lds64f(cs_addr + (64 + 8 * NB) * 4);
  return c;
}
template <int NB>
__device__ __forceinline__ void gu_piece(const float (&acc)[64], const float3 s1, const float3 s2, const CS c, uint32_t (&h)[16]) {
  h[4 * (NB >> 1) + 2 * (NB & 1) + 0] = pack_bf16(swiglu(acc[4 * NB + 0], acc[32 + 4 * NB + 0], c.a.x, c.b.x, s1),
                                                  swiglu(acc[4 * NB + 1], acc[32 + 4 * NB + 1], c.a.y, c.b.y, s1));
  h[4 * (NB >> 1) + 2 * (NB & 1) + 1] = pack_bf16(swiglu(acc[4 * NB + 2], acc[32 + 4 * NB + 2], c.a.x, c.b.x, s2),
                                                  swiglu(acc[4 * NB + 3], acc[32 + 4 * NB + 3], c.a.y, c.b.y, s2));
}

struct AttnOps { uint2 q1[5], q2[5], k[3][5], v[3][5]; };
template <int H>
__device__ __forceinline__ void attn_scores(const AttnOps& o, uint32_t mlo, bool p0, bool p1, float bias0, float bias1, uint32_t pm,
                                            uint32_t (&P)[4]) {
  const uint32_t mhi = ~mlo;
  const uint32_t m0l = (H == 0) ? 0xffffffffu : (H == 1) ? mhi : 0u;
  const uint32_t m0h = (H == 3) ? mhi : 0xffffffffu;
  const uint32_t m1l = (H == 0) ? mlo : 0xffffffffu;
  const uint32_t m1h = (H == 2) ? mlo : (H == 3) ? 0xffffffffu : 0u;
  float s[3][4];
#pragma unroll
  for (int kb = 0; kb < 3; kb++) {
    s[kb][0] = s[kb][1] = s[kb][2] = s[kb][3] = 0.f;
    mma16816(s[kb], o.q1[H].x & m0l, o.q2[H].x & m0l, o.q1[H].y & m0h, o.q2[H].y & m0h, o.k[kb][H].x, o.k[kb][H].y);
    mma16816(s[kb], o.q1[H + 1].x & m1l, o.q2[H + 1].x & m1l, o.q1[H + 1].y & m1h, o.q2[H + 1].y & m1h, o.k[kb][H + 1].x, o.k[kb][H + 1].y);
  }
  const float a0 = (p0 ? s[0][0] : s[1][0]) + bias0, a1 = (p1 ? s[0][1] : s[1][1]) + bias1;
  const float b0 = p0 ? s[1][2] : s[2][2], b1 = p1 ? s[1][3] : s[2][3];
  float m1 = fmaxf(a0, a1), m2 = fmaxf(b0, b1);
  m1 = fmaxf(m1, __shfl_xor_sync(0xffffffffu, m1, 1)); m2 = fmaxf(m2, __shfl_xor_sync(0xffffffffu, m2, 1));
  m1 = fmaxf(m1, __shfl_xor_sync(0xffffffffu, m1, 2)); m2 = fmaxf(m2, __shfl_xor_sync(0xffffffffu, m2, 2));
  const float cexp = 0.22360679774997896f * 1.4426950408889634f;
  const float o1 = -m1 * cexp, o2 = -m2 * cexp;
  const float e0 = ex2f(fmaf(a0, cexp, o1)), e1 = ex2f(fmaf(a1, cexp, o1));
  const float f0 = ex2f(fmaf(b0, cexp, o2)), f1 = ex2f(fmaf(b1, cexp, o2));
  float l1 = e0 + e1, l2 = f0 + f1;
  l1 += __shfl_xor_sync(0xffffffffu, l1, 1); l2 += __shfl_xor_sync(0xffffffffu, l2, 1);
  l1 += __shfl_xor_sync(0xffffffffu, l1, 2); l2 += __shfl_xor_sync(0xffffffffu, l2, 2);
  const float i1 = rcpf(l1), i2 = rcpf(l2);
  const uint32_t w1 = pack_bf16(e0 * i1, e1 * i1), w2 = pack_bf16(f0 * i2, f1 * i2);
  P[0] = w1 & pm;  P[1] = w1 & ~pm;
  P[2] = w2 & pm;  P[3] = w2 & ~pm;
}
__device__ __forceinline__ void attn_pv(const uint32_t (&P)[4], uint32_t v0, uint32_t v1, uint32_t v2, uint32_t& w1, uint32_t& w2) {
  float o[4] = {0.f, 0.f, 0.f, 0.f};
  mma16816(o, P[0], 0u, P[1], P[2], v0, v1);
  mma1688(o, 0u, P[3], v2);
  w1 = pack_bf16(o[0], o[1]);
  w2 = pack_bf16(o[2], o[3]);
}
__device__ __forceinline__ void attn_compute(const AttnOps& o, bool first, int g, int t, uint32_t (&of)[20]) {
  const bool lo = t < 2;
  const uint32_t mlo = lo ? 0xffffffffu : 0u;
  const bool p0 = 2 * t > g, p1 = 2 * t + 1 > g;
  const uint32_t pm = (p0 ? 0x0000ffffu : 0u) | (p1 ? 0xffff0000u : 0u);
  const float bias0 = (p0 && first) ? -INFINITY : 0.f, bias1 = (p1 && first) ? -INFINITY : 0.f;
  uint32_t P0[4], P1[4], P2[4], P3[4];
  attn_scores<0>(o, mlo, p0, p1, bias0, bias1, pm, P0);
  attn_scores<1>(o, mlo, p0, p1, bias0, bias1, pm, P1);
  attn_scores<2>(o, mlo, p0, p1, bias0, bias1, pm, P2);
  attn_scores<3>(o, mlo, p0, p1, bias0, bias1, pm, P3);
  uint32_t c1, c2;
  attn_pv(P0, movm(o.v[0][0].x), movm(o.v[1][0].x), movm(o.v[2][0].x), of[0], of[1]);
  attn_pv(P0, movm(o.v[0][0].y), movm(o.v[1][0].y), movm(o.v[2][0].y), of[2], of[3]);
  {
    const uint32_t t0 = movm(o.v[0][1].x), t1 = movm(o.v[1][1].x), t2 = movm(o.v[2][1].x);
    attn_pv(P0, t0, t1, t2, of[4], of[5]);
    attn_pv(P1, t0, t1, t2, c1, c2);
    of[4] = lo ? of[4] : c1; of[5] = lo ? of[5] : c2;
  }
  attn_pv(P1, movm(o.v[0][1].y), movm(o.v[1][1].y), movm(o.v[2][1].y), of[6], of[7]);
  attn_pv(P1, movm(o.v[0][2].x), movm(o.v[1][2].x), movm(o.v[2][2].x), of[8], of[9]);
  attn_pv(P2, movm(o.v[0][2].y), movm(o.v[1][2].y), movm(o.v[2][2].y), of[10], of[11]);
  attn_pv(P2, movm(o.v[0][3].x), movm(o.v[1][3].x), movm(o.v[2][3].x), of[12], of[13]);
  {
    const uint32_t t0 = movm(o.v[0][3].y), t1 = movm(o.v[1][3].y), t2 = movm(o.v[2][3].y);
    attn_pv(P2, t0, t1, t2, of[14], of[15]);
    attn_pv(P3, t0, t1, t2, c1, c2);
    of[14] = lo ? of[14] : c1; of[15] = lo ? of[15] : c2;
  }
  attn_pv(P3, movm(o.v[0][4].x), movm(o.v[1][4].x), movm(o.v[2][4].x), of[16], of[17]);
  attn_pv(P3, movm(o.v[0][4].y), movm(o.v[1][4].y), movm(o.v[2][4].y), of[18], of[19]);
}
__device__ __forceinline__ void halo_load(uint4 (&hv)[5], const uint4* src) {
#pragma unroll
  for (int b = 0; b < 5; b++) hv[b] = ld_tagged(src + 32 * b);
}

__device__ __forceinline__ void stat8(const uint4 v, float c, float& s, float& q) {
  float d;
  d = bf_lo(v.x) - c; s += d; q = fmaf(d, d, q);  d = bf_hi(v.x) - c; s += d; q = fmaf(d, d, q);
  d = bf_lo(v.y) - c; s += d; q = fmaf(d, d, q);  d = bf_hi(v.y) - c; s += d; q = fmaf(d, d, q);
  d = bf_lo(v.z) - c; s += d; q = fmaf(d, d, q);  d = bf_hi(v.z) - c; s += d; q = fmaf(d, d, q);
  d = bf_lo(v.w) - c; s += d; q = fmaf(d, d, q);  d = bf_hi(v.w) - c; s += d; q = fmaf(d, d, q);
}
__device__ __forceinline__ void add8(float* a, const uint4 v) {
  a[0] += bf_lo(v.x); a[1] += bf_hi(v.x); a[2] += bf_lo(v.y); a[3] += bf_hi(v.y);
  a[4] += bf_lo(v.z); a[5] += bf_hi(v.z); a[6] += bf_lo(v.w); a[7] += bf_hi(v.w);
}
__device__ __forceinline__ uint4 ldg128(const void* p) {
  uint4 v;
  asm volatile("ld.global.nc.L1::no_allocate.L2::128B.v4.u32 {%0, %1, %2, %3}, [%4];" : "=r"(v.x), "=r"(v.y), "=r"(v.z), "=r"(v.w) : "l"(p));
  return v;
}
__device__ __forceinline__ void col_task(float (&a)[16], const char* p, uint32_t step) {
#pragma unroll
  for (int i = 0; i < 8; i++) a[i] = 0.f;
  uint4 va[4], vb[4];
#pragma unroll
  for (int i = 0; i < 4; i++) { va[i] = ldg128(p); p += step; }
#pragma unroll 1
  for (int b = 0; b < 2; b++) {
#pragma unroll
    for (int i = 0; i < 4; i++) { vb[i] = ldg128(p); p += step; }
#pragma unroll
    for (int i = 0; i < 4; i++) add8(a, va[i]);
#pragma unroll
    for (int i = 0; i < 4; i++) { va[i] = ldg128(p); p += step; }
#pragma unroll
    for (int i = 0; i < 4; i++) add8(a, vb[i]);
  }
#pragma unroll
  for (int i = 0; i < 4; i++) add8(a, va[i]);
}
__device__ __forceinline__ uint32_t tagbad4(const uint4 u, uint32_t tag) { return (u.x ^ tag) | (u.y ^ tag) | (u.z ^ tag) | (u.w ^ tag); }
__device__ __forceinline__ uint4 fadd4(const uint4 a, const uint4 b) {
  return make_uint4(__float_as_uint(__uint_as_float(a.x) + __uint_as_float(b.x)), __float_as_uint(__uint_as_float(a.y) + __uint_as_float(b.y)),
                    __float_as_uint(__uint_as_float(a.z) + __uint_as_float(b.z)), __float_as_uint(__uint_as_float(a.w) + __uint_as_float(b.w)));
}
template <int N, int O>
__device__ __forceinline__ void treduce(float (&a)[16], int lane) {
  const bool up = lane & O;
#pragma unroll
  for (int i = 0; i < N / 2; i++) {
    const float keep = up ? a[N / 2 + i] : a[i], send = up ? a[i] : a[N / 2 + i];
    a[i] = keep + __shfl_xor_sync(0xffffffffu, send, O);
  }
}
__device__ __forceinline__ int col_of_lane(int lane) { return 8 * (lane & 1) + ((lane >> 4) & 1) * 4 + ((lane >> 3) & 1) * 2 + ((lane >> 2) & 1); }

__device__ __forceinline__ void g2_h_sc(float (&acc)[32], const uint32_t (&h)[16], uint32_t blo, uint32_t zero) {
  wgmma_rs64_sc(acc, h[0], h[1], h[2], h[3], blo, zero);
  wgmma_rs64(acc, h[4], h[5], h[6], h[7], blo + 128);
  wgmma_rs64(acc, h[8], h[9], h[10], h[11], blo + 256);
  wgmma_rs64(acc, h[12], h[13], h[14], h[15], blo + 384);
}
template <bool INIT>
__device__ __forceinline__ void g2_h(float (&acc)[32], const uint32_t (&h)[16], uint32_t blo) {
  if (INIT) wgmma_rs64_init(acc, h[0], h[1], h[2], h[3], blo);
  else      wgmma_rs64(acc, h[0], h[1], h[2], h[3], blo);
  wgmma_rs64(acc, h[4], h[5], h[6], h[7], blo + 128);
  wgmma_rs64(acc, h[8], h[9], h[10], h[11], blo + 256);
  wgmma_rs64(acc, h[12], h[13], h[14], h[15], blo + 384);
}
__device__ __forceinline__ void g2_o(float (&acc)[32], const uint32_t (&o)[20], uint32_t blo) {
#pragma unroll
  for (int s = 0; s < 5; s++) wgmma_rs64(acc, o[4 * s], o[4 * s + 1], o[4 * s + 2], o[4 * s + 3], blo + 1536 + 128 * s);
}
__device__ __forceinline__ uint4 pack8(const float (&acc)[32], int v) {
  return make_uint4(pack_bf16(acc[8 * v + 0], acc[8 * v + 1]), pack_bf16(acc[8 * v + 2], acc[8 * v + 3]),
                    pack_bf16(acc[8 * v + 4], acc[8 * v + 5]), pack_bf16(acc[8 * v + 6], acc[8 * v + 7]));
}
__device__ __forceinline__ uint32_t add_bf16x2(uint32_t a, uint32_t b) {
  uint32_t r;
  asm("add.rn.bf16x2 %0, %1, %2;" : "=r"(r) : "r"(a), "r"(b));
  return r;
}
__device__ __forceinline__ void store_tile(const uint4 (&f)[4], uint32_t ta, uint32_t tx) {
#pragma unroll
  for (int v = 0; v < 4; v++) stsm4(ta + (((2 * v) ^ tx) << 4), f[v]);
}

__global__ void __launch_bounds__(NTHREADS, 1)
fused_kernel(const __grid_constant__ CUtensorMap tmX, const __grid_constant__ CUtensorMap tmQA,
             const __grid_constant__ CUtensorMap tmQB, const __grid_constant__ CUtensorMap tmW1,
             const __grid_constant__ CUtensorMap tmW3, const __grid_constant__ CUtensorMap tmW2,
             const __grid_constant__ CUtensorMap tmWo, const __grid_constant__ CUtensorMap tmOut, const Params prm) {
  extern __shared__ __align__(1024) uint8_t smem_raw[];
  const uint32_t sb = smem_u32(smem_raw);
  const uint32_t bar0 = sb + SM_BAR;
  const int tid = threadIdx.x;
  const int warp = __shfl_sync(0xffffffffu, tid >> 5, 0);
  const int lane = tid & 31;
  const int j = blockIdx.x & 7, mt = blockIdx.x >> 3;
#define BAR(i) (bar0 + 8 * (i))

  if (warp >= 4) {
    asm volatile("setmaxnreg.inc.sync.aligned.u32 224;");
    const int w = (warp >> 2) - 1;
    const int tau = tid & 127;
    const int g = lane >> 2, t = lane & 3;
    const int half0 = 64 * mt + 16 * (warp & 3);
    const bool elect = tau == 0;
    const uint32_t xlo = (((sb + SM_X + w * 8192) & 0x3FFFFu) >> 4) | (1u << 16);
    const uint32_t ringq = (((sb + SM_RING) & 0x3FFFFu) >> 4) | (256u << 16);
    const uint32_t ringr = (((sb + SM_RING + 12288) & 0x3FFFFu) >> 4) | (64u << 16);
    const uint32_t ringg = (((sb + SM_RING) & 0x3FFFFu) >> 4) | (512u << 16);

    if (elect && w == 0) TSTAMP(6);
    float accm[96], accr[24];
#pragma unroll
    for (int i = 0; i < 96; i++) accm[i] = 0.f;
#pragma unroll
    for (int i = 0; i < 24; i++) accr[i] = 0.f;
    fence_regs(accm); fence_regs(accr);
    asm volatile("bar.sync 0, 384;" ::: "memory");
    asm volatile("barrier.cluster.arrive.relaxed.aligned;" ::: "memory");
#pragma unroll 1
    for (int ks = 0; ks < 20; ks++) {
      const int s = ks & 3;
      if ((ks & 1) == 0) mbar_wait(BAR(B_XFULL + (ks >> 1)), 0);
      mbar_wait(BAR(B_FULL + s), (ks >> 2) & 1);
      if (ks == 0 && elect && w == 0) TSTAMP(24);
      wg_fence();
      const uint32_t a = xlo + (ks >> 1) * 1024 + (ks & 1) * 4, b = ringq + s * 1024, br = ringr + s * 1024;
      wgmma_ss192(accm, a, b);
      wgmma_ss48r(accr, a, br);
      wgmma_ss192(accm, a + 2, b + 128);
      wgmma_ss48r(accr, a + 2, br + 32);
      wg_commit();
      wg_wait<1>();
      if (ks > 0 && elect) mbar_arrive(BAR(B_EMPTYQ + ((ks - 1) & 3)));
    }
    if (elect && w == 0) TSTAMP(25);
    asm volatile("barrier.cluster.wait.acquire.aligned;" ::: "memory");

    float accA[64], accB[64];
    uint32_t h0[16], h1[16], h2[16], of[20];
    AttnOps ao;

    uint32_t zero;
    asm volatile("mov.b32 %0, 0;" : "=r"(zero));
#define GU_STAGE0(ACC, G, FIRST)                                                       \
    {                                                                                  \
      mbar_wait(BAR(B_FULL + ((G) & 3)), ((G) >> 2) & 1);                              \
      wg_fence();                                                                      \
      const uint32_t a = xlo + (((G) - 20) % 10) * 1024, b = ringg + ((G) & 3) * 1024; \
      if ((FIRST) == 1) wgmma_ss128_init(ACC, a, b);                                   \
      else if ((FIRST) == 2) wgmma_ss128_sc(ACC, a, b, zero);                          \
      else wgmma_ss128(ACC, a, b);                                                     \
      wgmma_ss128(ACC, a + 2, b + 128);                                                \
      wgmma_ss128(ACC, a + 4, b + 256);                                                \
      wgmma_ss128(ACC, a + 6, b + 384);                                                \
      wg_commit();                                                                     \
    }
#define GU_REL(G)                                                                      \
    {                                                                                  \
      wg_wait<1>();                                                                    \
      if (elect) mbar_arrive(BAR(((G) <= 40 ? B_EMPTYQ : B_EMPTY) + (((G) - 1) & 3))); \
      if (elect) TSTAMP(64 + 32 * w + (G) - 20);                                       \
    }
#define GU_STAGE(ACC, G, FIRST) GU_STAGE0(ACC, G, FIRST) GU_REL(G)
#define PIN2(A, B) { const uint32_t z_ = __float_as_uint(pin(0.f, prm.zero)); A = __uint_as_float(__float_as_uint(A) ^ z_); B = __uint_as_float(__float_as_uint(B) ^ z_); }

    GU_STAGE(accA, 20, 1)
    fence_regs(accm); fence_regs(accr);
    GU_STAGE(accA, 21, 0)
    GU_STAGE0(accA, 22, 0)
    mbar_wait(BAR(B_EPI), 0);
    const uint32_t st_addr = sb + SM_CSB + (2 * (16 * (warp & 3) + g) + w) * 8;
    float2 s1 = lds64f(st_addr), s2 = lds64f(st_addr + 128);
    const uint32_t tag = __float_as_uint(s1.x) & 1u;
    const uint32_t csA = sb + SM_CSA + t * 8;
    uint4* halo = g_halo + ((j * 2 + w) * 64 + 4 * mt + (warp & 3)) * 160 + lane;
    CS ca, cb;
#define HALO_ST(p, v) st_tagged(p, v)
#define KV_LOAD(B) ca = qkv_cs<1, B>(csA); cb = qkv_cs<2, B>(csA);
#define KV_PIECE(B)                                                                    \
      PIN2(s1.y, s2.y)                                                                 \
      qkv_piece<1, B>(accm, accr, s1, s2, ca, ao.k[1][B], ao.k[2][B]);                 \
      qkv_piece<2, B>(accm, accr, s1, s2, cb, ao.v[1][B], ao.v[2][B]);                 \
      HALO_ST(halo + 32 * (B), make_uint4(set_tag(ao.k[2][B].x, tag), ao.k[2][B].y, ao.v[2][B].x, ao.v[2][B].y));
#define Q_LOAD(R, B) R = qkv_cs<0, B>(csA);
#define Q_PIECE(R, B) qkv_piece<0, B>(accm, accr, s1, s2, R, ao.q1[B], ao.q2[B]);
    KV_LOAD(0)
    GU_REL(22)
    KV_PIECE(0) KV_LOAD(1)
    GU_STAGE(accA, 23, 0)
    KV_PIECE(1) KV_LOAD(2)
    GU_STAGE(accA, 24, 0)
    KV_PIECE(2) KV_LOAD(3)
    GU_STAGE(accA, 25, 0)
    KV_PIECE(3) KV_LOAD(4)
    GU_STAGE(accA, 26, 0)
    KV_PIECE(4) Q_LOAD(ca, 0) Q_LOAD(cb, 1)
    GU_STAGE(accA, 27, 0)
    PIN2(s1.y, s2.y) Q_PIECE(ca, 0) Q_PIECE(cb, 1) Q_LOAD(ca, 2) Q_LOAD(cb, 3)
    GU_STAGE(accA, 28, 0)
    PIN2(s1.y, s2.y) Q_PIECE(ca, 2) Q_PIECE(cb, 3) Q_LOAD(ca, 4)
    const bool first = half0 == 0;
    uint4 hv[5];
    if (!first) halo_load(hv, halo - 160);
    else {
#pragma unroll
      for (int b = 0; b < 5; b++) hv[b] = make_uint4(tag, 0u, 0u, 0u);
    }
    GU_STAGE(accA, 29, 0)
    PIN2(s1.y, s2.y) Q_PIECE(ca, 4)
    __syncwarp();
    if (lane == 0) mbar_arrive(BAR(B_CSFREE));
    wg_wait<0>();
    fence_regs(accA);
    if (elect) mbar_arrive(BAR(B_EMPTYQ + 1));
    if (elect && w == 0) TSTAMP(26);
    {
      uint32_t it = 0;
#pragma unroll 1
      while ((((hv[0].x ^ tag) | (hv[1].x ^ tag) | (hv[2].x ^ tag) | (hv[3].x ^ tag) | (hv[4].x ^ tag)) & 1u) && ++it < SPIN_LIMIT)
        halo_load(hv, halo - 160);
#pragma unroll
      for (int b = 0; b < 5; b++) { ao.k[0][b] = make_uint2(hv[b].x, hv[b].y); ao.v[0][b] = make_uint2(hv[b].z, hv[b].w); }
    }
    mbar_wait(BAR(B_EPI), 0);
    attn_compute(ao, first, g, t, of);
    if (elect && w == 0) TSTAMP(22);

    float3 e1 = make_float3(s1.x * -1.4426950408889634f, s1.y, rcpf(s1.x * s1.x));
    float3 e2 = make_float3(s2.x * -1.4426950408889634f, s2.y, rcpf(s2.x * s2.x));
    const uint32_t csC = sb + SM_CSC + t * 8, csB = sb + SM_CSB + t * 8;
    GU_STAGE0(accB, 30, 1)
    mbar_wait(BAR(B_GU + 0), 0);
#define GU_PIECE(ACC, N, CSADDR, H) PIN2(e1.y, e2.y) GU_PIECE0(ACC, N, CSADDR, H)
#define GU_PIECE0(ACC, N, CSADDR, H) gu_piece<N>(ACC, e1, e2, ca, H); if ((N) < 7) ca = gu_cs<((N) < 7 ? (N) + 1 : 7)>(CSADDR);
    ca = gu_cs<0>(csC);
    GU_PIECE(accA, 0, csC, h0)
    GU_STAGE(accB, 31, 0) GU_PIECE(accA, 1, csC, h0)
    GU_STAGE(accB, 32, 0) GU_PIECE(accA, 2, csC, h0)
    GU_STAGE(accB, 33, 0) GU_PIECE(accA, 3, csC, h0)
    GU_STAGE(accB, 34, 0) GU_PIECE(accA, 4, csC, h0)
    GU_STAGE(accB, 35, 0) GU_PIECE(accA, 5, csC, h0)
    GU_STAGE(accB, 36, 0) GU_PIECE(accA, 6, csC, h0)
    GU_STAGE(accB, 37, 0) GU_PIECE(accA, 7, csC, h0)
    GU_STAGE(accB, 38, 0)
    GU_STAGE(accB, 39, 0)
    if (elect && w == 0) TSTAMP(27);

    float (&accC)[64] = accA;
    GU_STAGE(accC, 40, 2)
    fence_regs(accB);
    GU_STAGE(accC, 41, 0)
    GU_STAGE(accC, 42, 0)
    mbar_wait(BAR(B_GU + 1), 0);
    ca = gu_cs<0>(csB);
    GU_PIECE(accB, 0, csB, h1)
    GU_STAGE(accC, 43, 0) GU_PIECE(accB, 1, csB, h1)
    GU_STAGE(accC, 44, 0) GU_PIECE(accB, 2, csB, h1)
    GU_STAGE(accC, 45, 0) GU_PIECE(accB, 3, csB, h1)
    GU_STAGE(accC, 46, 0) GU_PIECE(accB, 4, csB, h1)
    GU_STAGE(accC, 47, 0) GU_PIECE(accB, 5, csB, h1)
    const int rho = j & 1;
    const uint32_t peer_bar0 = mapa(bar0, rho ^ 1);
    GU_STAGE(accC, 48, 0)
    if (elect) mbar_arrive_remote(peer_bar0 + 8 * B_REMPTY);
    GU_PIECE(accB, 6, csB, h1)
    GU_STAGE(accC, 49, 0)
    GU_PIECE(accB, 7, csB, h1)
    if (elect && w == 0) TSTAMP(28);

    float acc0[32], acc1[32];
    const uint32_t cdesc = ((sb & 0x3FFFFu) >> 4) | (1u << 16);
    constexpr uint32_t CS16 = CSLOT >> 4;

    const uint32_t csA2 = sb + SM_CSA + t * 8;
    mbar_wait(BAR(B_CFULL + 0), 0);
    wg_fence();
    g2_h<true>(acc0, h0, cdesc);
    g2_h<false>(acc0, h1, cdesc + 512);
    wg_commit();
    wg_wait<1>();
    if (elect) mbar_arrive(BAR(B_EMPTY + 1));
    fence_regs(accC);
    mbar_wait(BAR(B_GU + 2), 0);
    ca = gu_cs<0>(csA2);
    GU_PIECE0(accC, 0, csA2, h2) GU_PIECE0(accC, 1, csA2, h2)
    wg_fence();
    g2_o(acc0, of, cdesc);
    wgmma_rs64(acc0, h2[0], h2[1], h2[2], h2[3], cdesc + 1024);
    wg_commit();
    GU_PIECE0(accC, 2, csA2, h2) GU_PIECE0(accC, 3, csA2, h2) GU_PIECE0(accC, 4, csA2, h2) GU_PIECE0(accC, 5, csA2, h2)
    wg_fence();
    wgmma_rs64(acc0, h2[4], h2[5], h2[6], h2[7], cdesc + 1024 + 128);
    wgmma_rs64(acc0, h2[8], h2[9], h2[10], h2[11], cdesc + 1024 + 256);
    wg_commit();
    GU_PIECE0(accC, 6, csA2, h2) GU_PIECE0(accC, 7, csA2, h2)
    wg_fence();
    wgmma_rs64(acc0, h2[12], h2[13], h2[14], h2[15], cdesc + 1024 + 384);
    wg_commit();
    if (elect && w == 0) TSTAMP(29);

    const bool keeper = (w == rho);
    const uint32_t wofs = (warp & 3) * 2048;
    const uint32_t rbuf = sb + SM_RECV + wofs;
    const uint32_t peer_buf = mapa(rbuf, rho ^ 1) + lane * 16;
    const int trow = (lane & 7) + (lane & 8);
    const uint32_t tofs = trow * 128, tx = (lane >> 4) ^ (trow & 7);
    uint4 kp[4];
#define DBG2(C, K)
#define RBUF(K) (rbuf + ((K) & 3) * 8192)
#define PACK(ACC) { kp[0] = pack8(ACC, 0); kp[1] = pack8(ACC, 1); kp[2] = pack8(ACC, 2); kp[3] = pack8(ACC, 3); }
#define KEEP_LOAD(K)                                                                             \
      {                                                                                          \
        _Pragma("unroll")                                                                        \
        for (int v = 0; v < 4; v++) ku[v] = lds128(RBUF(K) + v * 512 + lane * 16);               \
      }
#define KEEP_TILE(K)                                                                             \
      {                                                                                          \
        _Pragma("unroll")                                                                        \
        for (int v = 0; v < 4; v++)                                                              \
          kp[v] = make_uint4(add_bf16x2(kp[v].x, ku[v].x), add_bf16x2(kp[v].y, ku[v].y), add_bf16x2(kp[v].z, ku[v].z), add_bf16x2(kp[v].w, ku[v].w)); \
        __syncwarp();                                                                            \
        store_tile(kp, RBUF(K) + tofs, tx);                                                      \
      }
#define KEEP_OUT(K)                                                                              \
      {                                                                                          \
        fence_async_smem();                                                                      \
        __syncwarp();                                                                            \
        if (elect_one()) { tma_add3d(&tmOut, RBUF(K), 64 * (K), half0, w); bulk_commit(); }      \
      }
#define SEND(ACC, K)                                                                             \
      {                                                                                          \
        _Pragma("unroll")                                                                        \
        for (int v = 0; v < 4; v++) st_async(peer_buf + ((K) & 3) * 8192 + v * 512, pack8(ACC, v), peer_bar0 + 8 * (B_RFULL + (K))); \
      }
#define RLAG 2
#define G2_CHUNK(CUR, PREV, C)                                                                   \
      {                                                                                          \
        const int s_ = (C) < 5 ? (C) : (C) - 5;                                                  \
        const uint32_t bl = cdesc + s_ * CS16;                                                   \
        DBG2(C, 0)                                                                               \
        const bool okx = keeper ? ((C) < 2 || mbar_test(BAR(B_RFULL + (C) - 2), 0))              \
                                : (((C) - 1 < RLAG && (C) > 1) || mbar_test(BAR(B_REMPTY + (C) - 1), 0)); \
        wg_fence();                                                                              \
        g2_h<true>(CUR, h0, bl);                                                                 \
        g2_h<false>(CUR, h1, bl + 512);                                                          \
        wg_commit();                                                                             \
        DBG2(C, 1)                                                                               \
        wg_wait<1>();                                                                            \
        DBG2(C, 2)                                                                               \
        if ((C) - 1 < 5 && elect) mbar_arrive(BAR(B_CEMPTY + (C) - 1));                          \
        fence_regs(PREV);                                                                        \
        if (keeper) {                                                                            \
          if ((C) >= 2) {                                                                        \
            uint4 ku[4];                                                                         \
            if (!okx) mbar_wait(BAR(B_RFULL + (C) - 2), 0);                                      \
            KEEP_LOAD((C) - 2)                                                                   \
              \
            if ((C) - 2 + RLAG < 9 && elect_one()) { bulk_wait_read<1>(); mbar_arrive_remote(peer_bar0 + 8 * (B_REMPTY + (C) - 2 + RLAG)); } \
            KEEP_TILE((C) - 2)                                                                   \
          }                                                                                      \
        } else {                                                                                 \
          if (!okx) mbar_wait(BAR(B_REMPTY + (C) - 1), 0);         \
          SEND(PREV, (C) - 1)                                                                    \
        }                                                                                        \
        DBG2(C, 4)                                                                               \
        wg_fence();                                                                              \
        g2_o(CUR, of, bl);                                                                       \
        g2_h<false>(CUR, h2, bl + 1024);                                                         \
        wg_commit();                                                                             \
        DBG2(C, 5)                                                                               \
        const int n_ = (C) + 1 < 5 ? (C) + 1 : (C) - 4;                                          \
        const bool okc = (C) == 9 || mbar_test(BAR(B_CFULL + n_), (C) + 1 < 5 ? 0 : 1);          \
        if (keeper) {                                                                            \
          if ((C) >= 2) {                                                                        \
            if ((C) == 2) mbar_wait(BAR(B_INIT), 0);                \
            KEEP_OUT((C) - 2)                                                                    \
          }                                                                                      \
          PACK(PREV)                                                                             \
        }                                                                                        \
        if (!okc) mbar_wait(BAR(B_CFULL + n_), (C) + 1 < 5 ? 0 : 1);                             \
        DBG2(C, 6)                                                                               \
      }                                                                                          \
      if (elect && w == 0) TSTAMP(32 + 3 * ((C) - 1));
    mbar_wait(BAR(B_CFULL + 1), 0);
    wg_wait<0>();
#pragma unroll 1
    for (int i2 = 0; i2 < 4; i2++) {
      const int c = 2 * i2 + 1;
      G2_CHUNK(acc1, acc0, c)
      G2_CHUNK(acc0, acc1, c + 1)
      wg_wait<0>();
    }
    G2_CHUNK(acc1, acc0, 9)
    if (keeper) {
      uint4 ku[4];
      mbar_wait(BAR(B_RFULL + 8), 0);
      KEEP_LOAD(8)
      KEEP_TILE(8)
      KEEP_OUT(8)
    }
    wg_wait<0>();
    fence_regs(acc1);
    if (elect && w == 0) TSTAMP(30);
    {
      PACK(acc1)
      const uint32_t b_ = sb + SM_LAST + w * 8192 + wofs;
      store_tile(kp, b_ + tofs, tx);
      fence_async_smem();
      __syncwarp();
      if (elect_one()) { tma_add3d(&tmOut, b_, 64 * 9, half0, w); bulk_commit(); bulk_wait_read<0>(); }
      if (elect) { TSTAMP(31); GSTAMP(63); }
      if (elect && !keeper) atomicAdd(&g_done[0], 1u);
    }
    } else {
    asm volatile("setmaxnreg.dec.sync.aligned.u32 56;");
    if (warp == 0) {
      if (elect_one()) {
        prefetch_tmap(&tmX); prefetch_tmap(&tmQA); prefetch_tmap(&tmQB);
#pragma unroll
        for (int i = 0; i < 3; i++) mbar_init(BAR(B_XFULL + i), 1);
#pragma unroll
        for (int i = 0; i < 4; i++) mbar_init(BAR(B_FULL + i), 1);
        asm volatile("fence.mbarrier_init.release.cluster;" ::: "memory");
#pragma unroll
        for (int ks = 0; ks < 4; ks++) {
          if ((ks & 1) == 0) {
            mbar_expect_tx(BAR(B_XFULL + (ks >> 1)), SLOT);
            tma3d(sb + SM_X + (ks >> 1) * SLOT, &tmX, 32 * ks, 64 * mt, 0, BAR(B_XFULL + (ks >> 1)));
            tma3d(sb + SM_X + (ks >> 1) * SLOT + 8192, &tmX, 32 * ks, 64 * mt, 1, BAR(B_XFULL + (ks >> 1)));
          }
          mbar_expect_tx(BAR(B_FULL + ks), QBYTES);
          tma3d(sb + SM_RING + ks * SLOT, &tmQA, 80 * j, 32 * ks, 0, BAR(B_FULL + ks));
          tma3d(sb + SM_RING + ks * SLOT + 12288, &tmQB, 80 * j + 64, 32 * ks, 0, BAR(B_FULL + ks));
        }
        mbar_expect_tx(BAR(B_XFULL + 2), SLOT);
        tma3d(sb + SM_X + 2 * SLOT, &tmX, 128, 64 * mt, 0, BAR(B_XFULL + 2));
        tma3d(sb + SM_X + 2 * SLOT + 8192, &tmX, 128, 64 * mt, 1, BAR(B_XFULL + 2));
        TSTAMP(5);
      }
      __syncwarp();
    } else if (warp == 1) {
      const int r = 128 * mt + 16 * j + (lane & 15);
      const __nv_bfloat16* p = prm.x + (size_t)r * D_ + 64 * (lane >> 4);
      asm volatile("prefetch.global.L2 [%0];" ::"l"(p));
    } else if (warp == 2) {
      const int r = 4 * mt + (lane >> 3), u = lane & 7;
      const __nv_bfloat16* p = prm.wqkv + (size_t)r * NQKV + 640 * (u >> 1) + 80 * j + 64 * (u & 1);
      if (u < 6) asm volatile("prefetch.global.L2 [%0];" ::"l"(p));
    } else if (warp == 3) {
      if (elect_one()) {
#pragma unroll
        for (int i = 3; i < B_COUNT; i++) {
          if (i >= B_FULL && i < B_EMPTY) continue;
          const uint32_t cnt = (i >= B_EMPTY && i < B_CFULL) ? 2u : (i >= B_CEMPTY && i < B_EPI) ? 2u : (i == B_REMPTY) ? 2u
                             : (i == B_CSFREE) ? 8u : (i >= B_EMPTYQ && i < B_XFREE) ? 3u : (i > B_INIT && i < B_EMPTYQ) ? 4u : 1u;
          mbar_init(BAR(i), cnt);
        }
#pragma unroll
        for (int i = 0; i < 9; i++) mbar_expect_tx(BAR(B_RFULL + i), 8192);
        asm volatile("fence.mbarrier_init.release.cluster;" ::: "memory");
      }
      __syncwarp();
    }
    asm volatile("bar.sync 0, 384;" ::: "memory");
    asm volatile("barrier.cluster.arrive.relaxed.aligned;" ::: "memory");
    const uint32_t ring = sb + SM_RING;
    if (warp == 0) {
      asm volatile("barrier.cluster.wait.acquire.aligned;" ::: "memory");
      if (elect_one()) {
        prefetch_tmap(&tmW1); prefetch_tmap(&tmW3); prefetch_tmap(&tmW2); prefetch_tmap(&tmWo); prefetch_tmap(&tmOut);
#pragma unroll 1
        for (int ks = 4; ks < 20; ks++) {
          if ((ks & 1) == 0 && ks < 18) {
            const int c = (ks >> 1) + 1;
            mbar_expect_tx(BAR(B_XFULL + c), SLOT);
            tma3d_mc(sb + SM_X + c * SLOT + (j & 1) * 8192, &tmX, 64 * c, 64 * mt, j & 1, BAR(B_XFULL + c));
          }
          const int s = ks & 3;
          mbar_wait(BAR(B_EMPTYQ + s), ((ks >> 2) & 1) ^ 1);
          mbar_expect_tx(BAR(B_FULL + s), QBYTES);
          tma3d(ring + s * SLOT, &tmQA, 80 * j, 32 * ks, 0, BAR(B_FULL + s));
          tma3d(ring + s * SLOT + 12288, &tmQB, 80 * j + 64, 32 * ks, 0, BAR(B_FULL + s));
        }
        TSTAMP(1);
#pragma unroll 1
        for (int g = 20; g < 50; g++) {
          const int s = g & 3, i = (g - 20) / 10, ks = (g - 20) - 10 * i;
          if (g < 44) mbar_wait(BAR(B_EMPTYQ + s), ((g >> 2) & 1) ^ 1);
          else        mbar_wait(BAR(B_EMPTY + s), (g >> 2) == 12);
          mbar_expect_tx(BAR(B_FULL + s), SLOT);
          tma2d(ring + s * SLOT, &tmW1, 192 * j + 64 * i, 64 * ks, BAR(B_FULL + s));
          tma2d(ring + s * SLOT + 8192, &tmW3, 192 * j + 64 * i, 64 * ks, BAR(B_FULL + s));
          if (g == 47) {
            mbar_wait(BAR(B_XFREE), 0);
            mbar_expect_tx(BAR(B_CFULL), CSLOT);
            tma2d(sb + 24576, &tmWo, 0, 80 * j, BAR(B_CFULL));
          }
        }
        TSTAMP(2);
        tma2d(sb, &tmW2, 0, 192 * j, BAR(B_CFULL));
#pragma unroll 1
        for (int c = 1; c < 10; c++) {
          if (c == 2) mbar_wait(BAR(B_EMPTY + 2), 1);
          if (c == 3) mbar_wait(BAR(B_EMPTY + 0), 0);
          if (c == 4) mbar_wait(BAR(B_EMPTY + 1), 0);
          const int s = c < 5 ? c : c - 5;
          if (c >= 5) mbar_wait(BAR(B_CEMPTY + s), 0);
          const uint32_t dst = sb + s * CSLOT;
          mbar_expect_tx(BAR(B_CFULL + s), CSLOT);
          tma2d(dst, &tmW2, 64 * c, 192 * j, BAR(B_CFULL + s));
          tma2d(dst + 24576, &tmWo, 64 * c, 80 * j, BAR(B_CFULL + s));
        }
        TSTAMP(3);
      }
    } else {
      const uint32_t tag = launch_tag();
      if (warp == 1) {
        const int par = lane >> 4, hf = (lane >> 3) & 1, il = lane & 7;
        const uint32_t a0 = sb + SM_X + par * 8192 + (8 * j + il) * 128;
        if (hf == 0) st_tagged64(&g_stats[128 * mt + 2 * (8 * j + il) + par], tag ^ 1u, 0u);
#pragma unroll
        for (int u = 0; u < 10; u++)
          st_tagged(g_halo + ((j * 2 + u / 5) * 64 + 4 * mt + 3) * 160 + 32 * (u % 5) + lane, make_uint4(tag ^ 1u, 0u, 0u, 0u));
        if (lane == 0) TSTAMP(15);
        mbar_wait(BAR(B_XFULL), 0);
        if (lane == 0) TSTAMP(7);
        const float c = bf_lo(lds32(a0 + il * 16));
        float s0 = 0.f, q0 = 0.f, s1 = 0.f, q1 = 0.f;
#pragma unroll 1
        for (int ch = 0; ch < 10; ch++) {
          mbar_wait(BAR(B_XFULL + ch), 0);
          const uint32_t a = a0 + ch * SLOT;
          const uint4 v0 = lds128(a + (((4 * hf + 0) ^ il) << 4)), v1 = lds128(a + (((4 * hf + 1) ^ il) << 4));
          const uint4 v2 = lds128(a + (((4 * hf + 2) ^ il) << 4)), v3 = lds128(a + (((4 * hf + 3) ^ il) << 4));
          stat8(v0, c, s0, q0); stat8(v1, c, s1, q1); stat8(v2, c, s0, q0); stat8(v3, c, s1, q1);
        }
        s0 += s1; q0 += q1;
        s0 += __shfl_xor_sync(0xffffffffu, s0, 8); q0 += __shfl_xor_sync(0xffffffffu, q0, 8);
        const float m = s0 * (1.0f / D_);
        const float var = fmaxf(fmaf(-m, m, q0 * (1.0f / D_)), 0.f);
        const float r = rsqrtf(var + 1e-5f);
        if (hf == 0) st_tagged64(&g_stats[128 * mt + 2 * (8 * j + il) + par], set_tag(__float_as_uint(r), tag), __float_as_uint(-(c + m)));
        __syncwarp();
        if (lane == 0) { mbar_arrive(BAR(B_PUB)); TSTAMP(8); }
      }
      float* const gdst = g_cs + j * 4 * 512;
      if (warp == 2) {
        if (lane < 16 && mt < 15) st_tagged32(gdst + 16 * mt + lane, tag ^ 1u);
        if (lane < 16) st_tagged32(gdst + 512 * (1 + (lane >> 3)) + 8 * mt + (lane & 7), tag ^ 1u);
        int g = 0;
#pragma unroll 1
        for (int rnd = 0; rnd < 3; rnd++) {
          uint32_t offe, offo, step;
          if (rnd == 0) {
            const int blk = min(mt, 14), c = lane & 7, rq = lane >> 3;
            if (blk < 12) {
              const uint32_t base = (blk >> 2) * 4096 + (c & 3) * 4, ch = 2 * (blk & 3) + (c >> 2);
              offe = base + (2 * rq) * 128 + ((ch ^ (2 * rq)) << 4);
              offo = base + (2 * rq + 1) * 128 + ((ch ^ (2 * rq + 1)) << 4);
              step = 1024;
            } else {
              const uint32_t base = 12288 + (blk - 12) * 1024 + (c & 3) * 4 + rq * 32;
              offe = base + ((c >> 2) << 4); offo = base + 128 + (((c >> 2) ^ 1) << 4);
              step = 256;
            }
          } else {
            const int rq = lane >> 2;
            offe = (mt >> 3) * 8192 + rq * 128 + (((mt & 7) ^ rq) << 4) + (lane & 3) * 4; offo = offe + 1024;
            step = 2048;
          }
          float a0 = 0.f, a1 = 0.f, a2 = 0.f, a3 = 0.f;
          const int gend = 20 + 10 * rnd;
#pragma unroll 1
          for (; g < gend; g++) {
            const int s = g & 3;
            mbar_wait(BAR(B_FULL + s), (g >> 2) & 1);
            const uint32_t pe = ring + s * SLOT + offe, po = ring + s * SLOT + offo;
            uint32_t v[8];
#pragma unroll
            for (int i = 0; i < 4; i++) { v[2 * i] = lds32(pe + i * step); v[2 * i + 1] = lds32(po + i * step); }
            __syncwarp();
            if (lane == 0) mbar_arrive(BAR(B_EMPTYQ + s));
#pragma unroll
            for (int i = 0; i < 4; i++) {
              a0 += bf_lo(v[2 * i]); a1 += bf_hi(v[2 * i]); a2 += bf_lo(v[2 * i + 1]); a3 += bf_hi(v[2 * i + 1]);
            }
          }
          a0 += a2; a1 += a3;
          const bool up = lane & 16;
          float v = (up ? a1 : a0) + __shfl_xor_sync(0xffffffffu, up ? a0 : a1, 16);
          v += __shfl_xor_sync(0xffffffffu, v, 8);
          if (rnd > 0) v += __shfl_xor_sync(0xffffffffu, v, 4);
          if (rnd == 0) { if (!(lane & 8) && mt < 15) st_tagged32(gdst + 16 * mt + 2 * (lane & 7) + (lane >> 4), set_tag(__float_as_uint(v), tag)); }
          else          { if (!(lane & 12)) st_tagged32(gdst + 512 * rnd + 8 * mt + 2 * (lane & 3) + (lane >> 4), set_tag(__float_as_uint(v), tag)); }
          __syncwarp();
          if (lane == 0) { mbar_arrive(BAR(rnd == 0 ? B_PUBQ : B_PUB + rnd)); TSTAMP(rnd == 0 ? 14 : 15 + rnd); }
        }
      }
      if (warp == 1) {
        const int gofs = 512 * 3 + 256 * (mt & 1) + 64 * (mt >> 3) + 16 * ((mt >> 1) & 3);
        if (!(lane & 2)) st_tagged32(gdst + gofs + col_of_lane(lane), tag ^ 1u);
        mbar_wait(BAR(B_CSFREE), 0);
        if (elect_one()) {
#pragma unroll 1
          for (int u = 0; u < (j < 2 ? 16 : 8); u++) {
            const int ch = j + (u & 8);
            tma_store3d(&tmOut, sb + SM_X + ch * SLOT + (u & 7) * 2048, 64 * ch, 64 * mt + 16 * (u & 3), (u >> 2) & 1);
          }
          bulk_commit();
          asm volatile("cp.async.bulk.wait_group 0;" ::: "memory");
          mbar_arrive(BAR(B_XFREE));
          fence_async();
          asm volatile("st.release.gpu.global.u32 [%0], %1;" ::"l"(&g_init[mt * 8 + j]), "r"(tag) : "memory");
          TSTAMP(13);
        }
        __syncwarp();
        const char* p = reinterpret_cast<const char*>(((mt >> 3) ? prm.w3 : prm.w1) + (size_t)(320 * (mt & 1) + (lane >> 1)) * F_ + 8 * (lane & 1) +
                                                      192 * j + 128 + 16 * ((mt >> 1) & 3));
        float a[16];
        col_task(a, p, 16 * F_ * 2);
        treduce<8, 16>(a, lane); treduce<4, 8>(a, lane); treduce<2, 4>(a, lane);
        const float v = a[0] + __shfl_xor_sync(0xffffffffu, a[0], 2);
        if (!(lane & 2)) st_tagged32(gdst + gofs + col_of_lane(lane), set_tag(__float_as_uint(v), tag));
        __syncwarp();
        if (lane == 0) { mbar_arrive(BAR(B_PUB + 3)); TSTAMP(18); }
      }
      if (warp == 3) {
        const uint4* cs = reinterpret_cast<const uint4*>(g_cs + j * 4 * 512);
        {
          mbar_wait(BAR(B_PUB), 0);
          const uint4* st = reinterpret_cast<const uint4*>(g_stats + 128 * mt);
          uint4 u0, u1;
          uint32_t it = 0;
#pragma unroll 1
          while (true) {
            u0 = ld_tagged(st + lane); u1 = ld_tagged(st + lane + 32);
            if (!__any_sync(0xffffffffu, ((u0.x ^ tag) | (u0.z ^ tag) | (u1.x ^ tag) | (u1.z ^ tag)) & 1u) || ++it > SPIN_LIMIT) break;
          }
          sts128(sb + SM_CSB + lane * 16, u0); sts128(sb + SM_CSB + (lane + 32) * 16, u1);
          const int l2 = min(lane + 32, 59);
          mbar_wait(BAR(B_PUBQ), 0);
          it = 0;
#pragma unroll 1
          while (true) {
            u0 = ld_tagged(cs + lane); u1 = ld_tagged(cs + l2);
            if (!__any_sync(0xffffffffu, (tagbad4(u0, tag) | tagbad4(u1, tag)) & 1u) || ++it > SPIN_LIMIT) break;
          }
          sts128(sb + SM_CSA + lane * 16, u0); sts128(sb + SM_CSA + l2 * 16, u1);
          __syncwarp();
          if (lane == 0) { mbar_arrive(BAR(B_EPI)); TSTAMP(9); }
        }
#pragma unroll 1
        for (int rnd = 1; rnd < 4; rnd++) {
          mbar_wait(BAR(B_PUB + rnd), 0);
          if (rnd == 2) mbar_wait(BAR(B_CSFREE), 0);
          uint4 u0, u1;
          uint32_t it = 0;
#pragma unroll 1
          while (true) {
            u0 = ld_tagged(cs + 128 * rnd + lane);
            u1 = u0;
            if (rnd == 3) u1 = ld_tagged(cs + 128 * rnd + 64 + lane);
            if (!__any_sync(0xffffffffu, (tagbad4(u0, tag) | tagbad4(u1, tag)) & 1u) || ++it > SPIN_LIMIT) break;
          }
          if (rnd == 3) u0 = fadd4(u0, u1);
          sts128(sb + (rnd == 1 ? SM_CSC : rnd == 2 ? SM_CSB : SM_CSA) + lane * 16, u0);
          __syncwarp();
          if (lane == 0) { mbar_arrive(BAR(B_GU + rnd - 1)); TSTAMP(19 + rnd - 1); }
        }
        {
          uint32_t it = 0;
#pragma unroll 1
          while (true) {
            unsigned v;
            asm volatile("ld.acquire.gpu.global.u32 %0, [%1];" : "=r"(v) : "l"(&g_init[mt * 8 + (lane & 7)]) : "memory");
            if (!__any_sync(0xffffffffu, (v ^ tag) & 1u) || ++it > SPIN_LIMIT) break;
          }
          __syncwarp();
          if (lane == 0) mbar_arrive(BAR(B_INIT));
        }
      }
    }
    __syncwarp();
    if (warp != 0) asm volatile("barrier.cluster.wait.acquire.aligned;" ::: "memory");
  }
#undef BAR
}

typedef CUresult (*EncodeFn)(CUtensorMap*, CUtensorMapDataType, cuuint32_t, void*, const cuuint64_t*, const cuuint64_t*,
                             const cuuint32_t*, const cuuint32_t*, CUtensorMapInterleave, CUtensorMapSwizzle,
                             CUtensorMapL2promotion, CUtensorMapFloatOOBfill);

CUtensorMap make_map(EncodeFn enc, const void* base, int rank, const cuuint64_t* dims, const cuuint64_t* strides, const cuuint32_t* box,
                     CUtensorMapSwizzle sw = CU_TENSOR_MAP_SWIZZLE_128B) {
  CUtensorMap m;
  const cuuint32_t es[3] = {1, 1, 1};
  enc(&m, CU_TENSOR_MAP_DATA_TYPE_BFLOAT16, (cuuint32_t)rank, const_cast<void*>(base), dims, strides, box, es,
      CU_TENSOR_MAP_INTERLEAVE_NONE, sw, CU_TENSOR_MAP_L2_PROMOTION_L2_128B, CU_TENSOR_MAP_FLOAT_OOB_FILL_NONE);
  return m;
}

}

extern "C" void kernel_launch(void* const* d_in, const int* in_sizes, int n_in, void* d_out, int out_size) {
  (void)in_sizes; (void)n_in; (void)out_size;
  static EncodeFn enc = nullptr;
  if (!enc) {
    void* fn = nullptr;
    cudaDriverEntryPointQueryResult q;
    cudaGetDriverEntryPoint("cuTensorMapEncodeTiled", &fn, cudaEnableDefault, &q);
    enc = (EncodeFn)fn;
    cudaFuncSetAttribute(fused_kernel, cudaFuncAttributeMaxDynamicSharedMemorySize, SM_TOTAL);
  }
  Params p;
  p.x = (const __nv_bfloat16*)d_in[0];
  p.wqkv = (const __nv_bfloat16*)d_in[1];
  p.w1 = (const __nv_bfloat16*)d_in[4];
  p.w3 = (const __nv_bfloat16*)d_in[5];
  p.out = (__nv_bfloat16*)d_out;
  p.zero = 0;
  const void* wo = d_in[2];
  const void* w2 = d_in[6];

  CUtensorMap tmX, tmQA, tmQB, tmW1, tmW3, tmW2, tmWo, tmOut;
  { const cuuint64_t d[3] = {D_, S_ / 2, 2}, s[2] = {D_ * 4, D_ * 2}; const cuuint32_t b[3] = {64, 64, 1}; tmX = make_map(enc, p.x, 3, d, s, b); }
  { const cuuint64_t d[3] = {D_, S_ / 2, 2}, s[2] = {D_ * 4, D_ * 2}; const cuuint32_t b[3] = {64, 16, 1}; tmOut = make_map(enc, p.out, 3, d, s, b); }
  { const cuuint64_t d[3] = {D_, D_, 3}, s[2] = {NQKV * 2, D_ * 2};
    const cuuint32_t b[3] = {64, 32, 3}; tmQA = make_map(enc, p.wqkv, 3, d, s, b);
    const cuuint32_t b2[3] = {16, 32, 3}; tmQB = make_map(enc, p.wqkv, 3, d, s, b2, CU_TENSOR_MAP_SWIZZLE_32B); }
  { const cuuint64_t d[2] = {F_, D_}, s[1] = {F_ * 2}; const cuuint32_t b[2] = {64, 64}; tmW1 = make_map(enc, p.w1, 2, d, s, b); tmW3 = make_map(enc, p.w3, 2, d, s, b); }
  { const cuuint64_t d[2] = {D_, F_}, s[1] = {D_ * 2}; const cuuint32_t b[2] = {64, 192}; tmW2 = make_map(enc, w2, 2, d, s, b); }
  { const cuuint64_t d[2] = {D_, D_}, s[1] = {D_ * 2}; const cuuint32_t b[2] = {64, 80}; tmWo = make_map(enc, wo, 2, d, s, b); }

  cudaLaunchConfig_t cfg = {};
  cfg.gridDim = dim3(128);
  cfg.blockDim = dim3(NTHREADS);
  cfg.dynamicSmemBytes = SM_TOTAL;
  cfg.stream = cudaStreamPerThread;
  cudaLaunchAttribute at[1];
  at[0].id = cudaLaunchAttributeClusterDimension;
  at[0].val.clusterDim.x = 2; at[0].val.clusterDim.y = 1; at[0].val.clusterDim.z = 1;
  cfg.attrs = at; cfg.numAttrs = 1;
  cudaLaunchKernelEx(&cfg, fused_kernel, tmX, tmQA, tmQB, tmW1, tmW3, tmW2, tmWo, tmOut, p);
}
```

```cpp
#define USE_TANH
#define UNROLL_G2
#include <cuda_runtime.h>
#include <cuda_bf16.h>
#include <cuda.h>
#include <stdint.h>

namespace {

constexpr int S_ = 2048, D_ = 640, F_ = 1536, NQKV = 1920;
constexpr int NTHREADS = 384;

constexpr int SM_X    = 0;
constexpr int SM_RING = 163840;
constexpr int SLOT    = 16384;
constexpr int QBYTES  = 15360;
constexpr int CSLOT   = 34816;
constexpr int SM_RECV = 196608;
constexpr int SM_LAST = 174080;
constexpr int SM_CSA  = 229376;
constexpr int SM_CSB  = SM_CSA + 960;
constexpr int SM_CSC  = SM_CSB + 1024;
constexpr int SM_BAR  = 231872;
constexpr int SM_TAG  = SM_BAR + 568;
constexpr int SM_TOTAL = 232448;
constexpr int B_XFULL = 0, B_FULL = 10, B_EMPTY = 14, B_CFULL = 18, B_CEMPTY = 23, B_EPI = 28, B_GU = 29, B_PUB = 32,
              B_RFULL = 36, B_CSFREE = 45, B_REMPTY = 46, B_INIT = 47, B_EMPTYQ = 57, B_XFREE = 61, B_PUBQ = 62, B_TAG = 63, B_COUNT = 64;

#define W0_AT 46
#define HALO_DEP ao.q2[2].y
constexpr uint32_t SPIN_LIMIT = 1u << 17;
constexpr uint32_t DESC_HI   = 0x40000040u;
constexpr uint32_t DESC_HI32 = 0xC0000010u;

__device__ uint4  g_halo[8 * 2 * 64 * 5 * 32];
__device__ unsigned g_init[16 * 8];
__device__ float2 g_stats[S_];
__device__ float  g_cs[8 * 4 * 512];
__device__ unsigned g_done[32];
#define TSTAMP(id) do {} while (0)
#define GSTAMP(id) do {} while (0)
#define TVALUE(id, v) do { (void)(v); } while (0)

struct Params {
  const __nv_bfloat16* x;
  const __nv_bfloat16* wqkv;
  const __nv_bfloat16* w1;
  const __nv_bfloat16* w3;
  __nv_bfloat16* out;
  uint32_t zero;
};

__device__ __forceinline__ uint32_t smem_u32(const void* p) { return (uint32_t)__cvta_generic_to_shared(p); }
__device__ __forceinline__ bool elect_one() {
  uint32_t p;
  asm volatile("{\n.reg .pred P;\nelect.sync _|P, 0xffffffff;\nselp.u32 %0, 1, 0, P;\n}" : "=r"(p));
  return p != 0;
}
__device__ __forceinline__ void mbar_init(uint32_t bar, uint32_t cnt) {
  asm volatile("mbarrier.init.shared::cta.b64 [%0], %1;" ::"r"(bar), "r"(cnt) : "memory");
}
__device__ __forceinline__ void mbar_expect_tx(uint32_t bar, uint32_t bytes) {
  asm volatile("mbarrier.arrive.expect_tx.shared::cta.b64 _, [%0], %1;" ::"r"(bar), "r"(bytes) : "memory");
}
__device__ __forceinline__ void mbar_arrive(uint32_t bar) {
  asm volatile("mbarrier.arrive.shared::cta.b64 _, [%0];" ::"r"(bar) : "memory");
}
__device__ __forceinline__ bool mbar_try(uint32_t bar, uint32_t parity) {
  uint32_t ok;
  asm volatile("{\n.reg .pred p;\nmbarrier.try_wait.parity.shared::cta.b64 p, [%1], %2;\nselp.u32 %0, 1, 0, p;\n}"
               : "=r"(ok) : "r"(bar), "r"(parity) : "memory");
  return ok != 0;
}
__device__ __forceinline__ void mbar_wait(uint32_t bar, uint32_t parity) {
  uint32_t it = 0;
#pragma unroll 1
  while (!mbar_try(bar, parity)) { if (++it > SPIN_LIMIT) break; }
}
__device__ __forceinline__ bool mbar_test(uint32_t bar, uint32_t parity) {
  uint32_t ok;
  asm volatile("{\n.reg .pred p;\nmbarrier.test_wait.parity.shared::cta.b64 p, [%1], %2;\nselp.u32 %0, 1, 0, p;\n}"
               : "=r"(ok) : "r"(bar), "r"(parity) : "memory");
  return ok != 0;
}
__device__ __forceinline__ void tma2d(uint32_t dst, const CUtensorMap* m, int c0, int c1, uint32_t bar) {
  asm volatile("cp.async.bulk.tensor.2d.shared::cluster.global.mbarrier::complete_tx::bytes [%0], [%1, {%3, %4}], [%2];"
               ::"r"(dst), "l"(m), "r"(bar), "r"(c0), "r"(c1) : "memory");
}
__device__ __forceinline__ void tma3d(uint32_t dst, const CUtensorMap* m, int c0, int c1, int c2, uint32_t bar) {
  asm volatile("cp.async.bulk.tensor.3d.shared::cluster.global.mbarrier::complete_tx::bytes [%0], [%1, {%3, %4, %5}], [%2];"
               ::"r"(dst), "l"(m), "r"(bar), "r"(c0), "r"(c1), "r"(c2) : "memory");
}
__device__ __forceinline__ void tma3d_mc(uint32_t dst, const CUtensorMap* m, int c0, int c1, int c2, uint32_t bar) {
  asm volatile("cp.async.bulk.tensor.3d.shared::cluster.global.mbarrier::complete_tx::bytes.multicast::cluster [%0], [%1, {%3, %4, %5}], [%2], %6;"
               ::"r"(dst), "l"(m), "r"(bar), "r"(c0), "r"(c1), "r"(c2), "h"((uint16_t)3) : "memory");
}
__device__ __forceinline__ void tma_store3d(const CUtensorMap* m, uint32_t src, int c0, int c1, int c2) {
  asm volatile("cp.async.bulk.tensor.3d.global.shared::cta.tile.bulk_group [%0, {%2, %3, %4}], [%1];"
               ::"l"(m), "r"(src), "r"(c0), "r"(c1), "r"(c2) : "memory");
}
__device__ __forceinline__ void tma_add3d(const CUtensorMap* m, uint32_t src, int c0, int c1, int c2) {
  asm volatile("cp.reduce.async.bulk.tensor.3d.global.shared::cta.add.tile.bulk_group [%0, {%2, %3, %4}], [%1];"
               ::"l"(m), "r"(src), "r"(c0), "r"(c1), "r"(c2) : "memory");
}
__device__ __forceinline__ void bulk_to_peer(uint32_t dst_cluster, uint32_t src, uint32_t bytes, uint32_t bar_cluster) {
  asm volatile("cp.async.bulk.shared::cluster.shared::cta.mbarrier::complete_tx::bytes [%0], [%1], %2, [%3];"
               ::"r"(dst_cluster), "r"(src), "r"(bytes), "r"(bar_cluster) : "memory");
}
__device__ __forceinline__ void bulk_commit() { asm volatile("cp.async.bulk.commit_group;" ::: "memory"); }
template <int N> __device__ __forceinline__ void bulk_wait_read() { asm volatile("cp.async.bulk.wait_group.read %0;" ::"n"(N) : "memory"); }
__device__ __forceinline__ void fence_async() { asm volatile("fence.proxy.async;" ::: "memory"); }
__device__ __forceinline__ void fence_async_smem() { asm volatile("fence.proxy.async.shared::cta;" ::: "memory"); }
__device__ __forceinline__ void stsm4(uint32_t addr, const uint4 v) {
  asm volatile("stmatrix.sync.aligned.m8n8.x4.shared.b16 [%0], {%1, %2, %3, %4};" ::"r"(addr), "r"(v.x), "r"(v.y), "r"(v.z), "r"(v.w) : "memory");
}
__device__ __forceinline__ void prefetch_tmap(const CUtensorMap* m) {
  asm volatile("prefetch.tensormap [%0];" ::"l"(m) : "memory");
}
__device__ __forceinline__ void wg_fence() { asm volatile("wgmma.fence.sync.aligned;" ::: "memory"); }
__device__ __forceinline__ void wg_commit() { asm volatile("wgmma.commit_group.sync.aligned;" ::: "memory"); }
template <int N> __device__ __forceinline__ void wg_wait() { asm volatile("wgmma.wait_group.sync.aligned %0;" ::"n"(N) : "memory"); }
template <int N> __device__ __forceinline__ void fence_regs(float (&a)[N]) {
#pragma unroll
  for (int i = 0; i < N; i++) asm volatile("" : "+f"(a[i]) :: "memory");
}
__device__ __forceinline__ uint32_t pack_bf16(float lo, float hi) {
  uint32_t r;
  asm("cvt.rn.bf16x2.f32 %0, %1, %2;" : "=r"(r) : "f"(hi), "f"(lo));
  return r;
}
__device__ __forceinline__ float bf_lo(uint32_t w) { return __uint_as_float(w << 16); }
__device__ __forceinline__ float bf_hi(uint32_t w) { return __uint_as_float(w & 0xffff0000u); }
__device__ __forceinline__ float2 lds64f(uint32_t addr) {
  float2 v;
  asm volatile("ld.shared.v2.f32 {%0, %1}, [%2];" : "=f"(v.x), "=f"(v.y) : "r"(addr));
  return v;
}
__device__ __forceinline__ uint2 lds64u(uint32_t addr) {
  uint2 v;
  asm volatile("ld.shared.v2.b32 {%0, %1}, [%2];" : "=r"(v.x), "=r"(v.y) : "r"(addr) : "memory");
  return v;
}
__device__ __forceinline__ uint32_t lds32(uint32_t addr) {
  uint32_t v;
  asm volatile("ld.shared.b32 %0, [%1];" : "=r"(v) : "r"(addr) : "memory");
  return v;
}
__device__ __forceinline__ uint4 lds128(uint32_t addr) {
  uint4 v;
  asm volatile("ld.shared.v4.b32 {%0, %1, %2, %3}, [%4];" : "=r"(v.x), "=r"(v.y), "=r"(v.z), "=r"(v.w) : "r"(addr) : "memory");
  return v;
}
__device__ __forceinline__ void sts128(uint32_t addr, uint4 v) {
  asm volatile("st.shared.v4.b32 [%0], {%1, %2, %3, %4};" ::"r"(addr), "r"(v.x), "r"(v.y), "r"(v.z), "r"(v.w) : "memory");
}
__device__ __forceinline__ float ex2f(float x) { float y; asm("ex2.approx.ftz.f32 %0, %1;" : "=f"(y) : "f"(x)); return y; }
__device__ __forceinline__ float rcpf(float x) { float y; asm("rcp.approx.ftz.f32 %0, %1;" : "=f"(y) : "f"(x)); return y; }
__device__ __forceinline__ void mma16816(float (&c)[4], uint32_t a0, uint32_t a1, uint32_t a2, uint32_t a3, uint32_t b0, uint32_t b1) {
  asm volatile("mma.sync.aligned.m16n8k16.row.col.f32.bf16.bf16.f32 {%0,%1,%2,%3}, {%4,%5,%6,%7}, {%8,%9}, {%0,%1,%2,%3};"
               : "+f"(c[0]), "+f"(c[1]), "+f"(c[2]), "+f"(c[3]) : "r"(a0), "r"(a1), "r"(a2), "r"(a3), "r"(b0), "r"(b1));
}
__device__ __forceinline__ void mma16816_c(float (&d)[4], uint32_t a0, uint32_t a1, uint32_t a2, uint32_t a3, uint32_t b0, uint32_t b1, float ci) {
  asm volatile("mma.sync.aligned.m16n8k16.row.col.f32.bf16.bf16.f32 {%0,%1,%2,%3}, {%4,%5,%6,%7}, {%8,%9}, {%10,%10,%10,%10};"
               : "=f"(d[0]), "=f"(d[1]), "=f"(d[2]), "=f"(d[3]) : "r"(a0), "r"(a1), "r"(a2), "r"(a3), "r"(b0), "r"(b1), "f"(ci));
}
__device__ __forceinline__ void mma1688(float (&c)[4], uint32_t a0, uint32_t a1, uint32_t b0) {
  asm volatile("mma.sync.aligned.m16n8k8.row.col.f32.bf16.bf16.f32 {%0,%1,%2,%3}, {%4,%5}, {%6}, {%0,%1,%2,%3};"
               : "+f"(c[0]), "+f"(c[1]), "+f"(c[2]), "+f"(c[3]) : "r"(a0), "r"(a1), "r"(b0));
}
__device__ __forceinline__ uint32_t movm(uint32_t a) {
  uint32_t d;
  asm volatile("movmatrix.sync.aligned.m8n8.trans.b16 %0, %1;" : "=r"(d) : "r"(a));
  return d;
}
__device__ __forceinline__ uint32_t mapa(uint32_t addr, uint32_t rank) {
  uint32_t r;
  asm("mapa.shared::cluster.u32 %0, %1, %2;" : "=r"(r) : "r"(addr), "r"(rank));
  return r;
}
__device__ __forceinline__ void mbar_arrive_remote(uint32_t cluster_addr) {
  asm volatile("mbarrier.arrive.shared::cluster.b64 _, [%0];" ::"r"(cluster_addr) : "memory");
}
__device__ __forceinline__ void st_async(uint32_t cluster_addr, uint4 v, uint32_t cluster_bar) {
  asm volatile("st.async.weak.shared::cluster.mbarrier::complete_tx::bytes.v4.b32 [%0], {%1, %2, %3, %4}, [%5];"
               ::"r"(cluster_addr), "r"(v.x), "r"(v.y), "r"(v.z), "r"(v.w), "r"(cluster_bar) : "memory");
}
__device__ __forceinline__ void st_tagged(void* p, uint4 v) {
  asm volatile("{\n.reg .b128 r;\nmov.b128 r, {%1, %2};\nst.relaxed.gpu.global.b128 [%0], r;\n}"
               ::"l"(p), "l"(((uint64_t)v.y << 32) | v.x), "l"(((uint64_t)v.w << 32) | v.z) : "memory");
}
__device__ __forceinline__ uint4 ld_tagged(const void* p) {
  uint64_t a, b;
  asm volatile("{\n.reg .b128 r;\nld.relaxed.gpu.global.b128 r, [%2];\nmov.b128 {%0, %1}, r;\n}" : "=l"(a), "=l"(b) : "l"(p) : "memory");
  return make_uint4((uint32_t)a, (uint32_t)(a >> 32), (uint32_t)b, (uint32_t)(b >> 32));
}
__device__ __forceinline__ void st_tagged64(void* p, uint32_t x, uint32_t y) {
  asm volatile("st.relaxed.gpu.global.b64 [%0], %1;" ::"l"(p), "l"(((uint64_t)y << 32) | x) : "memory");
}
__device__ __forceinline__ void st_tagged32(void* p, uint32_t x) {
  asm volatile("st.relaxed.gpu.global.b32 [%0], %1;" ::"l"(p), "r"(x) : "memory");
}
__device__ __forceinline__ uint32_t set_tag(uint32_t w, uint32_t tag) { return (w & 0xfffffffeu) | tag; }
__device__ __forceinline__ uint32_t launch_tag() {
  unsigned v;
  asm volatile("ld.relaxed.gpu.global.u32 %0, [%1];" : "=r"(v) : "l"(&g_done[0]) : "memory");
  return ((v >> 7) + 1) & 1u;
}

__device__ __forceinline__ void wgmma_rs64_sc(float (&d)[32], uint32_t a0, uint32_t a1, uint32_t a2, uint32_t a3, uint32_t blo, uint32_t sc) {
  asm volatile("{\n.reg .pred p;\n.reg .b64 db;\n"
    "setp.ne.b32 p, %38, 0;\n"
    "mov.b64 db, {%36, %37};\n"
    "wgmma.mma_async.sync.aligned.m64n64k16.f32.bf16.bf16 {%0, %1, %2, %3, %4, %5, %6, %7, %8, %9, %10, %11, %12, %13, %14, %15, %16, %17, %18, %19, %20, %21, %22, %23, %24, %25, %26, %27, %28, %29, %30, %31}, {%32,%33,%34,%35}, db, p, 1, 1, 1;\n}\n"
    :
        "+f"(d[0]), "+f"(d[1]), "+f"(d[2]), "+f"(d[3]), "+f"(d[4]), "+f"(d[5]), "+f"(d[6]), "+f"(d[7]),
        "+f"(d[8]), "+f"(d[9]), "+f"(d[10]), "+f"(d[11]), "+f"(d[12]), "+f"(d[13]), "+f"(d[14]), "+f"(d[15]),
        "+f"(d[16]), "+f"(d[17]), "+f"(d[18]), "+f"(d[19]), "+f"(d[20]), "+f"(d[21]), "+f"(d[22]), "+f"(d[23]),
        "+f"(d[24]), "+f"(d[25]), "+f"(d[26]), "+f"(d[27]), "+f"(d[28]), "+f"(d[29]), "+f"(d[30]), "+f"(d[31])
    : "r"(a0), "r"(a1), "r"(a2), "r"(a3), "r"(blo), "n"(DESC_HI), "r"(sc));
}
__device__ __forceinline__ void wgmma_ss192(float (&d)[96], uint32_t alo, uint32_t blo) {
  asm volatile("{\n.reg .pred p;\n.reg .b64 da, db;\n"
    "setp.eq.b32 p, 0, 0;\n"
    "mov.b64 da, {%96, %98};\nmov.b64 db, {%97, %99};\n"
    "wgmma.mma_async.sync.aligned.m64n192k16.f32.bf16.bf16 {%0, %1, %2, %3, %4, %5, %6, %7, %8, %9, %10, %11, %12, %13, %14, %15, %16, %17, %18, %19, %20, %21, %22, %23, %24, %25, %26, %27, %28, %29, %30, %31, %32, %33, %34, %35, %36, %37, %38, %39, %40, %41, %42, %43, %44, %45, %46, %47, %48, %49, %50, %51, %52, %53, %54, %55, %56, %57, %58, %59, %60, %61, %62, %63, %64, %65, %66, %67, %68, %69, %70, %71, %72, %73, %74, %75, %76, %77, %78, %79, %80, %81, %82, %83, %84, %85, %86, %87, %88, %89, %90, %91, %92, %93, %94, %95}, da, db, p, 1, 1, 0, 1;\n}\n"
    :
        "+f"(d[0]), "+f"(d[1]), "+f"(d[2]), "+f"(d[3]), "+f"(d[4]), "+f"(d[5]), "+f"(d[6]), "+f"(d[7]),
        "+f"(d[8]), "+f"(d[9]), "+f"(d[10]), "+f"(d[11]), "+f"(d[12]), "+f"(d[13]), "+f"(d[14]), "+f"(d[15]),
        "+f"(d[16]), "+f"(d[17]), "+f"(d[18]), "+f"(d[19]), "+f"(d[20]), "+f"(d[21]), "+f"(d[22]), "+f"(d[23]),
        "+f"(d[24]), "+f"(d[25]), "+f"(d[26]), "+f"(d[27]), "+f"(d[28]), "+f"(d[29]), "+f"(d[30]), "+f"(d[31]),
        "+f"(d[32]), "+f"(d[33]), "+f"(d[34]), "+f"(d[35]), "+f"(d[36]), "+f"(d[37]), "+f"(d[38]), "+f"(d[39]),
        "+f"(d[40]), "+f"(d[41]), "+f"(d[42]), "+f"(d[43]), "+f"(d[44]), "+f"(d[45]), "+f"(d[46]), "+f"(d[47]),
        "+f"(d[48]), "+f"(d[49]), "+f"(d[50]), "+f"(d[51]), "+f"(d[52]), "+f"(d[53]), "+f"(d[54]), "+f"(d[55]),
        "+f"(d[56]), "+f"(d[57]), "+f"(d[58]), "+f"(d[59]), "+f"(d[60]), "+f"(d[61]), "+f"(d[62]), "+f"(d[63]),
        "+f"(d[64]), "+f"(d[65]), "+f"(d[66]), "+f"(d[67]), "+f"(d[68]), "+f"(d[69]), "+f"(d[70]), "+f"(d[71]),
        "+f"(d[72]), "+f"(d[73]), "+f"(d[74]), "+f"(d[75]), "+f"(d[76]), "+f"(d[77]), "+f"(d[78]), "+f"(d[79]),
        "+f"(d[80]), "+f"(d[81]), "+f"(d[82]), "+f"(d[83]), "+f"(d[84]), "+f"(d[85]), "+f"(d[86]), "+f"(d[87]),
        "+f"(d[88]), "+f"(d[89]), "+f"(d[90]), "+f"(d[91]), "+f"(d[92]), "+f"(d[93]), "+f"(d[94]), "+f"(d[95])
    : "r"(alo), "r"(blo), "n"(DESC_HI), "n"(DESC_HI));
}
__device__ __forceinline__ void wgmma_ss48r(float (&d)[24], uint32_t alo, uint32_t blo) {
  asm volatile("{\n.reg .pred p;\n.reg .b64 da, db;\n"
    "setp.eq.b32 p, 0, 0;\n"
    "mov.b64 da, {%24, %26};\nmov.b64 db, {%25, %27};\n"
    "wgmma.mma_async.sync.aligned.m64n48k16.f32.bf16.bf16 {%0, %1, %2, %3, %4, %5, %6, %7, %8, %9, %10, %11, %12, %13, %14, %15, %16, %17, %18, %19, %20, %21, %22, %23}, da, db, p, 1, 1, 0, 1;\n}\n"
    :
        "+f"(d[0]), "+f"(d[1]), "+f"(d[2]), "+f"(d[3]), "+f"(d[4]), "+f"(d[5]), "+f"(d[6]), "+f"(d[7]),
        "+f"(d[8]), "+f"(d[9]), "+f"(d[10]), "+f"(d[11]), "+f"(d[12]), "+f"(d[13]), "+f"(d[14]), "+f"(d[15]),
        "+f"(d[16]), "+f"(d[17]), "+f"(d[18]), "+f"(d[19]), "+f"(d[20]), "+f"(d[21]), "+f"(d[22]), "+f"(d[23])
    : "r"(alo), "r"(blo), "n"(DESC_HI), "n"(DESC_HI32));
}
__device__ __forceinline__ void wgmma_ss128_init(float (&d)[64], uint32_t alo, uint32_t blo) {
  asm volatile("{\n.reg .pred p;\n.reg .b64 da, db;\n"
    "setp.ne.b32 p, 0, 0;\n"
    "mov.b64 da, {%64, %66};\nmov.b64 db, {%65, %66};\n"
    "wgmma.mma_async.sync.aligned.m64n128k16.f32.bf16.bf16 {%0, %1, %2, %3, %4, %5, %6, %7, %8, %9, %10, %11, %12, %13, %14, %15, %16, %17, %18, %19, %20, %21, %22, %23, %24, %25, %26, %27, %28, %29, %30, %31, %32, %33, %34, %35, %36, %37, %38, %39, %40, %41, %42, %43, %44, %45, %46, %47, %48, %49, %50, %51, %52, %53, %54, %55, %56, %57, %58, %59, %60, %61, %62, %63}, da, db, p, 1, 1, 0, 1;\n}\n"
    :
        "=f"(d[0]), "=f"(d[1]), "=f"(d[2]), "=f"(d[3]), "=f"(d[4]), "=f"(d[5]), "=f"(d[6]), "=f"(d[7]),
        "=f"(d[8]), "=f"(d[9]), "=f"(d[10]), "=f"(d[11]), "=f"(d[12]), "=f"(d[13]), "=f"(d[14]), "=f"(d[15]),
        "=f"(d[16]), "=f"(d[17]), "=f"(d[18]), "=f"(d[19]), "=f"(d[20]), "=f"(d[21]), "=f"(d[22]), "=f"(d[23]),
        "=f"(d[24]), "=f"(d[25]), "=f"(d[26]), "=f"(d[27]), "=f"(d[28]), "=f"(d[29]), "=f"(d[30]), "=f"(d[31]),
        "=f"(d[32]), "=f"(d[33]), "=f"(d[34]), "=f"(d[35]), "=f"(d[36]), "=f"(d[37]), "=f"(d[38]), "=f"(d[39]),
        "=f"(d[40]), "=f"(d[41]), "=f"(d[42]), "=f"(d[43]), "=f"(d[44]), "=f"(d[45]), "=f"(d[46]), "=f"(d[47]),
        "=f"(d[48]), "=f"(d[49]), "=f"(d[50]), "=f"(d[51]), "=f"(d[52]), "=f"(d[53]), "=f"(d[54]), "=f"(d[55]),
        "=f"(d[56]), "=f"(d[57]), "=f"(d[58]), "=f"(d[59]), "=f"(d[60]), "=f"(d[61]), "=f"(d[62]), "=f"(d[63])
    : "r"(alo), "r"(blo), "n"(DESC_HI));
}
__device__ __forceinline__ void wgmma_ss128_sc(float (&d)[64], uint32_t alo, uint32_t blo, uint32_t sc) {
  asm volatile("{\n.reg .pred p;\n.reg .b64 da, db;\n"
    "setp.ne.b32 p, %67, 0;\n"
    "mov.b64 da, {%64, %66};\nmov.b64 db, {%65, %66};\n"
    "wgmma.mma_async.sync.aligned.m64n128k16.f32.bf16.bf16 {%0, %1, %2, %3, %4, %5, %6, %7, %8, %9, %10, %11, %12, %13, %14, %15, %16, %17, %18, %19, %20, %21, %22, %23, %24, %25, %26, %27, %28, %29, %30, %31, %32, %33, %34, %35, %36, %37, %38, %39, %40, %41, %42, %43, %44, %45, %46, %47, %48, %49, %50, %51, %52, %53, %54, %55, %56, %57, %58, %59, %60, %61, %62, %63}, da, db, p, 1, 1, 0, 1;\n}\n"
    :
        "+f"(d[0]), "+f"(d[1]), "+f"(d[2]), "+f"(d[3]), "+f"(d[4]), "+f"(d[5]), "+f"(d[6]), "+f"(d[7]),
        "+f"(d[8]), "+f"(d[9]), "+f"(d[10]), "+f"(d[11]), "+f"(d[12]), "+f"(d[13]), "+f"(d[14]), "+f"(d[15]),
        "+f"(d[16]), "+f"(d[17]), "+f"(d[18]), "+f"(d[19]), "+f"(d[20]), "+f"(d[21]), "+f"(d[22]), "+f"(d[23]),
        "+f"(d[24]), "+f"(d[25]), "+f"(d[26]), "+f"(d[27]), "+f"(d[28]), "+f"(d[29]), "+f"(d[30]), "+f"(d[31]),
        "+f"(d[32]), "+f"(d[33]), "+f"(d[34]), "+f"(d[35]), "+f"(d[36]), "+f"(d[37]), "+f"(d[38]), "+f"(d[39]),
        "+f"(d[40]), "+f"(d[41]), "+f"(d[42]), "+f"(d[43]), "+f"(d[44]), "+f"(d[45]), "+f"(d[46]), "+f"(d[47]),
        "+f"(d[48]), "+f"(d[49]), "+f"(d[50]), "+f"(d[51]), "+f"(d[52]), "+f"(d[53]), "+f"(d[54]), "+f"(d[55]),
        "+f"(d[56]), "+f"(d[57]), "+f"(d[58]), "+f"(d[59]), "+f"(d[60]), "+f"(d[61]), "+f"(d[62]), "+f"(d[63])
    : "r"(alo), "r"(blo), "n"(DESC_HI), "r"(sc));
}
__device__ __forceinline__ void wgmma_ss128(float (&d)[64], uint32_t alo, uint32_t blo) {
  asm volatile("{\n.reg .pred p;\n.reg .b64 da, db;\n"
    "setp.eq.b32 p, 0, 0;\n"
    "mov.b64 da, {%64, %66};\nmov.b64 db, {%65, %67};\n"
    "wgmma.mma_async.sync.aligned.m64n128k16.f32.bf16.bf16 {%0, %1, %2, %3, %4, %5, %6, %7, %8, %9, %10, %11, %12, %13, %14, %15, %16, %17, %18, %19, %20, %21, %22, %23, %24, %25, %26, %27, %28, %29, %30, %31, %32, %33, %34, %35, %36, %37, %38, %39, %40, %41, %42, %43, %44, %45, %46, %47, %48, %49, %50, %51, %52, %53, %54, %55, %56, %57, %58, %59, %60, %61, %62, %63}, da, db, p, 1, 1, 0, 1;\n}\n"
    :
        "+f"(d[0]), "+f"(d[1]), "+f"(d[2]), "+f"(d[3]), "+f"(d[4]), "+f"(d[5]), "+f"(d[6]), "+f"(d[7]),
        "+f"(d[8]), "+f"(d[9]), "+f"(d[10]), "+f"(d[11]), "+f"(d[12]), "+f"(d[13]), "+f"(d[14]), "+f"(d[15]),
        "+f"(d[16]), "+f"(d[17]), "+f"(d[18]), "+f"(d[19]), "+f"(d[20]), "+f"(d[21]), "+f"(d[22]), "+f"(d[23]),
        "+f"(d[24]), "+f"(d[25]), "+f"(d[26]), "+f"(d[27]), "+f"(d[28]), "+f"(d[29]), "+f"(d[30]), "+f"(d[31]),
        "+f"(d[32]), "+f"(d[33]), "+f"(d[34]), "+f"(d[35]), "+f"(d[36]), "+f"(d[37]), "+f"(d[38]), "+f"(d[39]),
        "+f"(d[40]), "+f"(d[41]), "+f"(d[42]), "+f"(d[43]), "+f"(d[44]), "+f"(d[45]), "+f"(d[46]), "+f"(d[47]),
        "+f"(d[48]), "+f"(d[49]), "+f"(d[50]), "+f"(d[51]), "+f"(d[52]), "+f"(d[53]), "+f"(d[54]), "+f"(d[55]),
        "+f"(d[56]), "+f"(d[57]), "+f"(d[58]), "+f"(d[59]), "+f"(d[60]), "+f"(d[61]), "+f"(d[62]), "+f"(d[63])
    : "r"(alo), "r"(blo), "n"(DESC_HI), "n"(DESC_HI));
}
__device__ __forceinline__ void wgmma_rs64_init(float (&d)[32], uint32_t a0, uint32_t a1, uint32_t a2, uint32_t a3, uint32_t blo) {
  asm volatile("{\n.reg .pred p;\n.reg .b64 db;\n"
    "setp.ne.b32 p, 0, 0;\n"
    "mov.b64 db, {%36, %37};\n"
    "wgmma.mma_async.sync.aligned.m64n64k16.f32.bf16.bf16 {%0, %1, %2, %3, %4, %5, %6, %7, %8, %9, %10, %11, %12, %13, %14, %15, %16, %17, %18, %19, %20, %21, %22, %23, %24, %25, %26, %27, %28, %29, %30, %31}, {%32,%33,%34,%35}, db, p, 1, 1, 1;\n}\n"
    :
        "=f"(d[0]), "=f"(d[1]), "=f"(d[2]), "=f"(d[3]), "=f"(d[4]), "=f"(d[5]), "=f"(d[6]), "=f"(d[7]),
        "=f"(d[8]), "=f"(d[9]), "=f"(d[10]), "=f"(d[11]), "=f"(d[12]), "=f"(d[13]), "=f"(d[14]), "=f"(d[15]),
        "=f"(d[16]), "=f"(d[17]), "=f"(d[18]), "=f"(d[19]), "=f"(d[20]), "=f"(d[21]), "=f"(d[22]), "=f"(d[23]),
        "=f"(d[24]), "=f"(d[25]), "=f"(d[26]), "=f"(d[27]), "=f"(d[28]), "=f"(d[29]), "=f"(d[30]), "=f"(d[31])
    : "r"(a0), "r"(a1), "r"(a2), "r"(a3), "r"(blo), "n"(DESC_HI));
}
__device__ __forceinline__ void wgmma_rs64(float (&d)[32], uint32_t a0, uint32_t a1, uint32_t a2, uint32_t a3, uint32_t blo) {
  asm volatile("{\n.reg .pred p;\n.reg .b64 db;\n"
    "setp.eq.b32 p, 0, 0;\n"
    "mov.b64 db, {%36, %37};\n"
    "wgmma.mma_async.sync.aligned.m64n64k16.f32.bf16.bf16 {%0, %1, %2, %3, %4, %5, %6, %7, %8, %9, %10, %11, %12, %13, %14, %15, %16, %17, %18, %19, %20, %21, %22, %23, %24, %25, %26, %27, %28, %29, %30, %31}, {%32,%33,%34,%35}, db, p, 1, 1, 1;\n}\n"
    :
        "+f"(d[0]), "+f"(d[1]), "+f"(d[2]), "+f"(d[3]), "+f"(d[4]), "+f"(d[5]), "+f"(d[6]), "+f"(d[7]),
        "+f"(d[8]), "+f"(d[9]), "+f"(d[10]), "+f"(d[11]), "+f"(d[12]), "+f"(d[13]), "+f"(d[14]), "+f"(d[15]),
        "+f"(d[16]), "+f"(d[17]), "+f"(d[18]), "+f"(d[19]), "+f"(d[20]), "+f"(d[21]), "+f"(d[22]), "+f"(d[23]),
        "+f"(d[24]), "+f"(d[25]), "+f"(d[26]), "+f"(d[27]), "+f"(d[28]), "+f"(d[29]), "+f"(d[30]), "+f"(d[31])
    : "r"(a0), "r"(a1), "r"(a2), "r"(a3), "r"(blo), "n"(DESC_HI));
}

__device__ __forceinline__ float pin(float x, uint32_t zero) {
  uint32_t c;
  asm volatile("mov.u32 %0, %%clock;" : "=r"(c) :: "memory");
  return __uint_as_float(__float_as_uint(x) ^ (c & zero));
}
struct CS { float2 a, b; };
template <int S, int B>
__device__ __forceinline__ CS qkv_cs(uint32_t cs_addr) {
  constexpr int COL = (B < 4) ? 64 * S + 16 * B : 192 + 16 * S;
  CS c; c.a = lds64f(cs_addr + COL * 4); c.b = lds64f(cs_addr + (COL + 8) * 4);
  return c;
}
template <int S, int B>
__device__ __forceinline__ void qkv_piece(const float (&am)[96], const float (&ar)[24], float2 s1, float2 s2, const CS c,
                                          uint2& w1, uint2& w2) {
  float a[8];
#pragma unroll
  for (int i = 0; i < 8; i++) a[i] = (B < 4) ? am[(B < 4 ? 32 * S + 8 * B : 0) + i] : ar[(B < 4 ? 0 : 8 * S) + i];
  w1.x = pack_bf16(s1.x * fmaf(s1.y, c.a.x, a[0]), s1.x * fmaf(s1.y, c.a.y, a[1]));
  w2.x = pack_bf16(s2.x * fmaf(s2.y, c.a.x, a[2]), s2.x * fmaf(s2.y, c.a.y, a[3]));
  w1.y = pack_bf16(s1.x * fmaf(s1.y, c.b.x, a[4]), s1.x * fmaf(s1.y, c.b.y, a[5]));
  w2.y = pack_bf16(s2.x * fmaf(s2.y, c.b.x, a[6]), s2.x * fmaf(s2.y, c.b.y, a[7]));
}
template <int B>
__device__ __forceinline__ void q_piece(const float (&am)[96], const float (&ar)[24], float m1, float m2, const CS c, uint2& w1, uint2& w2) {
  float a[8];
#pragma unroll
  for (int i = 0; i < 8; i++) a[i] = (B < 4) ? am[(B < 4 ? 8 * B : 0) + i] : ar[i];
  w1.x = pack_bf16(fmaf(m1, c.a.x, a[0]), fmaf(m1, c.a.y, a[1]));
  w2.x = pack_bf16(fmaf(m2, c.a.x, a[2]), fmaf(m2, c.a.y, a[3]));
  w1.y = pack_bf16(fmaf(m1, c.b.x, a[4]), fmaf(m1, c.b.y, a[5]));
  w2.y = pack_bf16(fmaf(m2, c.b.x, a[6]), fmaf(m2, c.b.y, a[7]));
}
__device__ __forceinline__ float tanhf_hw(float x) { float y; asm("tanh.approx.f32 %0, %1;" : "=f"(y) : "f"(x)); return y; }
__device__ __forceinline__ float swiglu(float ag, float au, float cg, float cu, const float3 s) {
  const float g = fmaf(s.y, cg, ag), u = fmaf(s.y, cu, au);
  const float t = tanhf_hw(g * s.x);
  return (g * u) * fmaf(t, s.z, s.z);
}
template <int NB>
__device__ __forceinline__ CS gu_cs(uint32_t cs_addr) {
  CS c; c.a = lds64f(cs_addr + (8 * NB) * 4); c.b = lds64f(cs_addr + (64 + 8 * NB) * 4);
  return c;
}
template <int NB>
__device__ __forceinline__ void gu_piece(const float (&acc)[64], const float3 s1, const float3 s2, const CS c, uint32_t (&h)[16]) {
  h[4 * (NB >> 1) + 2 * (NB & 1) + 0] = pack_bf16(swiglu(acc[4 * NB + 0], acc[32 + 4 * NB + 0], c.a.x, c.b.x, s1),
                                                  swiglu(acc[4 * NB + 1], acc[32 + 4 * NB + 1], c.a.y, c.b.y, s1));
  h[4 * (NB >> 1) + 2 * (NB & 1) + 1] = pack_bf16(swiglu(acc[4 * NB + 2], acc[32 + 4 * NB + 2], c.a.x, c.b.x, s2),
                                                  swiglu(acc[4 * NB + 3], acc[32 + 4 * NB + 3], c.a.y, c.b.y, s2));
}

struct AttnOps { uint2 q1[5], q2[5], k[3][5], v[3][5]; };
template <int H>
__device__ __forceinline__ void attn_qk(const AttnOps& o, const uint2 (&k)[5], uint32_t mlo, float ci, float (&s)[4]) {
  const uint32_t m = (H & 1) ? ~mlo : mlo;
  if (H == 0) { mma16816_c(s, o.q1[0].x, o.q2[0].x, o.q1[0].y, o.q2[0].y, k[0].x, k[0].y, ci); mma1688(s, o.q1[1].x & m, o.q2[1].x & m, k[1].x); }
  if (H == 1) { mma16816_c(s, o.q1[1].y, o.q2[1].y, o.q1[2].x, o.q2[2].x, k[1].y, k[2].x, ci); mma1688(s, o.q1[1].x & m, o.q2[1].x & m, k[1].x); }
  if (H == 2) { mma16816_c(s, o.q1[2].y, o.q2[2].y, o.q1[3].x, o.q2[3].x, k[2].y, k[3].x, ci); mma1688(s, o.q1[3].y & m, o.q2[3].y & m, k[3].y); }
  if (H == 3) { mma16816_c(s, o.q1[4].x, o.q2[4].x, o.q1[4].y, o.q2[4].y, k[4].x, k[4].y, ci); mma1688(s, o.q1[3].y & m, o.q2[3].y & m, k[3].y); }
}
template <int H>
__device__ __forceinline__ float4 attn_own(const AttnOps& o, uint32_t mlo, bool p0, bool p1) {
  float s1[4], s2[4];
  attn_qk<H>(o, o.k[1], mlo, 0.f, s1);
  attn_qk<H>(o, o.k[2], mlo, 0.f, s2);
  return make_float4(s1[0], s1[1], p0 ? s1[2] : s2[2], p1 ? s1[3] : s2[3]);
}
template <int H>
__device__ __forceinline__ void attn_softmax(const AttnOps& o, const float4 sc, uint32_t mlo, bool p0, bool p1, float bias, float c1, float c2,
                                             uint32_t pm, uint32_t (&P)[4]) {
  float s0[4];
  attn_qk<H>(o, o.k[0], mlo, bias, s0);
  const float a0 = p0 ? s0[0] : sc.x, a1 = p1 ? s0[1] : sc.y;
  const float b0 = sc.z, b1 = sc.w;
  float m1 = fmaxf(a0, a1), m2 = fmaxf(b0, b1);
  m1 = fmaxf(m1, __shfl_xor_sync(0xffffffffu, m1, 1)); m2 = fmaxf(m2, __shfl_xor_sync(0xffffffffu, m2, 1));
  m1 = fmaxf(m1, __shfl_xor_sync(0xffffffffu, m1, 2)); m2 = fmaxf(m2, __shfl_xor_sync(0xffffffffu, m2, 2));
  const float o1 = -m1 * c1, o2 = -m2 * c2;
  const float e0 = ex2f(fmaf(a0, c1, o1)), e1 = ex2f(fmaf(a1, c1, o1));
  const float f0 = ex2f(fmaf(b0, c2, o2)), f1 = ex2f(fmaf(b1, c2, o2));
  float l1 = e0 + e1, l2 = f0 + f1;
  l1 += __shfl_xor_sync(0xffffffffu, l1, 1); l2 += __shfl_xor_sync(0xffffffffu, l2, 1);
  l1 += __shfl_xor_sync(0xffffffffu, l1, 2); l2 += __shfl_xor_sync(0xffffffffu, l2, 2);
  const float i1 = rcpf(l1), i2 = rcpf(l2);
  const uint32_t w1 = pack_bf16(e0 * i1, e1 * i1), w2 = pack_bf16(f0 * i2, f1 * i2);
  P[0] = w1 & pm;  P[1] = w1 & ~pm;
  P[2] = w2 & pm;  P[3] = w2 & ~pm;
}
__device__ __forceinline__ void attn_pv(const uint32_t (&P)[4], uint32_t v0, uint32_t v1, uint32_t v2, uint32_t& w1, uint32_t& w2) {
  float o[4];
  mma16816_c(o, P[1], P[2], 0u, P[3], v1, v2, 0.f);
  mma1688(o, P[0], 0u, v0);
  w1 = pack_bf16(o[0], o[1]);
  w2 = pack_bf16(o[2], o[3]);
}
__device__ __forceinline__ void attn_compute(const AttnOps& o, const float4 (&sc)[4], bool first, int g, int t, float r1, float r2,
                                             uint32_t (&of)[20]) {
  const bool lo = t < 2;
  const uint32_t mlo = lo ? 0xffffffffu : 0u;
  const bool p0 = 2 * t > g, p1 = 2 * t + 1 > g;
  const uint32_t pm = (p0 ? 0x0000ffffu : 0u) | (p1 ? 0xffff0000u : 0u);
  const float bias = first ? -INFINITY : 0.f;
  const float cexp = 0.22360679774997896f * 1.4426950408889634f;
  const float c1 = cexp * r1, c2 = cexp * r2;
  uint32_t P0[4], P1[4], P2[4], P3[4];
  attn_softmax<0>(o, sc[0], mlo, p0, p1, bias, c1, c2, pm, P0);
  attn_softmax<1>(o, sc[1], mlo, p0, p1, bias, c1, c2, pm, P1);
  attn_softmax<2>(o, sc[2], mlo, p0, p1, bias, c1, c2, pm, P2);
  attn_softmax<3>(o, sc[3], mlo, p0, p1, bias, c1, c2, pm, P3);
  uint32_t c1_, c2_;
  attn_pv(P0, o.v[0][0].x, o.v[1][0].x, o.v[2][0].x, of[0], of[1]);
  attn_pv(P0, o.v[0][0].y, o.v[1][0].y, o.v[2][0].y, of[2], of[3]);
  attn_pv(P0, o.v[0][1].x, o.v[1][1].x, o.v[2][1].x, of[4], of[5]);
  attn_pv(P1, o.v[0][1].x, o.v[1][1].x, o.v[2][1].x, c1_, c2_);
  of[4] = lo ? of[4] : c1_; of[5] = lo ? of[5] : c2_;
  attn_pv(P1, o.v[0][1].y, o.v[1][1].y, o.v[2][1].y, of[6], of[7]);
  attn_pv(P1, o.v[0][2].x, o.v[1][2].x, o.v[2][2].x, of[8], of[9]);
  attn_pv(P2, o.v[0][2].y, o.v[1][2].y, o.v[2][2].y, of[10], of[11]);
  attn_pv(P2, o.v[0][3].x, o.v[1][3].x, o.v[2][3].x, of[12], of[13]);
  attn_pv(P2, o.v[0][3].y, o.v[1][3].y, o.v[2][3].y, of[14], of[15]);
  attn_pv(P3, o.v[0][3].y, o.v[1][3].y, o.v[2][3].y, c1_, c2_);
  of[14] = lo ? of[14] : c1_; of[15] = lo ? of[15] : c2_;
  attn_pv(P3, o.v[0][4].x, o.v[1][4].x, o.v[2][4].x, of[16], of[17]);
  attn_pv(P3, o.v[0][4].y, o.v[1][4].y, o.v[2][4].y, of[18], of[19]);
}
__device__ __forceinline__ void halo_load(uint64_t (&hv)[10], const uint4* src) {
#pragma unroll
  for (int b = 0; b < 5; b++)
    asm volatile("{\n.reg .b128 r;\nld.relaxed.gpu.global.b128 r, [%2];\nmov.b128 {%0, %1}, r;\n}"
                 : "=l"(hv[2 * b]), "=l"(hv[2 * b + 1]) : "l"(src + 32 * b) : "memory");
}
__device__ __forceinline__ void halo_reload(uint64_t (&hv)[10], const uint4* src) {
#pragma unroll
  for (int b = 0; b < 5; b++)
    asm volatile("{\n.reg .b128 r;\nld.relaxed.gpu.global.b128 r, [%2];\nmov.b128 {%0, %1}, r;\n}"
                 : "+l"(hv[2 * b]), "+l"(hv[2 * b + 1]) : "l"(src + 32 * b) : "memory");
}
__device__ __forceinline__ uint32_t halo_bad(const uint64_t (&hv)[10], uint32_t t) {
  uint32_t a[5];
#pragma unroll
  for (int i = 0; i < 5; i++)
    asm("lop3.b32 %0, %1, %2, %3, 0x7e;" : "=r"(a[i]) : "r"((uint32_t)hv[2 * i]), "r"((uint32_t)hv[2 * i + 1]), "r"(t));
  return a[0] | a[1] | a[2] | a[3] | a[4];
}

__device__ __forceinline__ void stat8(const uint4 v, float c, float& s, float& q) {
  float d;
  d = bf_lo(v.x) - c; s += d; q = fmaf(d, d, q);  d = bf_hi(v.x) - c; s += d; q = fmaf(d, d, q);
  d = bf_lo(v.y) - c; s += d; q = fmaf(d, d, q);  d = bf_hi(v.y) - c; s += d; q = fmaf(d, d, q);
  d = bf_lo(v.z) - c; s += d; q = fmaf(d, d, q);  d = bf_hi(v.z) - c; s += d; q = fmaf(d, d, q);
  d = bf_lo(v.w) - c; s += d; q = fmaf(d, d, q);  d = bf_hi(v.w) - c; s += d; q = fmaf(d, d, q);
}
__device__ __forceinline__ void add8(float* a, const uint4 v) {
  a[0] += bf_lo(v.x); a[1] += bf_hi(v.x); a[2] += bf_lo(v.y); a[3] += bf_hi(v.y);
  a[4] += bf_lo(v.z); a[5] += bf_hi(v.z); a[6] += bf_lo(v.w); a[7] += bf_hi(v.w);
}
__device__ __forceinline__ uint4 ldg128(const void* p) {
  uint4 v;
  asm volatile("ld.global.nc.L1::no_allocate.L2::128B.v4.u32 {%0, %1, %2, %3}, [%4];" : "=r"(v.x), "=r"(v.y), "=r"(v.z), "=r"(v.w) : "l"(p));
  return v;
}
__device__ __forceinline__ void col_task(float (&a)[16], const char* p, uint32_t step) {
#pragma unroll
  for (int i = 0; i < 8; i++) a[i] = 0.f;
  uint4 va[4], vb[4];
#pragma unroll
  for (int i = 0; i < 4; i++) { va[i] = ldg128(p); p += step; }
#pragma unroll 1
  for (int b = 0; b < 2; b++) {
#pragma unroll
    for (int i = 0; i < 4; i++) { vb[i] = ldg128(p); p += step; }
#pragma unroll
    for (int i = 0; i < 4; i++) add8(a, va[i]);
#pragma unroll
    for (int i = 0; i < 4; i++) { va[i] = ldg128(p); p += step; }
#pragma unroll
    for (int i = 0; i < 4; i++) add8(a, vb[i]);
  }
#pragma unroll
  for (int i = 0; i < 4; i++) add8(a, va[i]);
}
__device__ __forceinline__ uint32_t tagbad4(const uint4 u, uint32_t tag) { return (u.x ^ tag) | (u.y ^ tag) | (u.z ^ tag) | (u.w ^ tag); }
__device__ __forceinline__ uint4 fadd4(const uint4 a, const uint4 b) {
  return make_uint4(__float_as_uint(__uint_as_float(a.x) + __uint_as_float(b.x)), __float_as_uint(__uint_as_float(a.y) + __uint_as_float(b.y)),
                    __float_as_uint(__uint_as_float(a.z) + __uint_as_float(b.z)), __float_as_uint(__uint_as_float(a.w) + __uint_as_float(b.w)));
}
template <int N, int O>
__device__ __forceinline__ void treduce(float (&a)[16], int lane) {
  const bool up = lane & O;
#pragma unroll
  for (int i = 0; i < N / 2; i++) {
    const float keep = up ? a[N / 2 + i] : a[i], send = up ? a[i] : a[N / 2 + i];
    a[i] = keep + __shfl_xor_sync(0xffffffffu, send, O);
  }
}
__device__ __forceinline__ int col_of_lane(int lane) { return 8 * (lane & 1) + ((lane >> 4) & 1) * 4 + ((lane >> 3) & 1) * 2 + ((lane >> 2) & 1); }

__device__ __forceinline__ void g2_h_sc(float (&acc)[32], const uint32_t (&h)[16], uint32_t blo, uint32_t zero) {
  wgmma_rs64_sc(acc, h[0], h[1], h[2], h[3], blo, zero);
  wgmma_rs64(acc, h[4], h[5], h[6], h[7], blo + 128);
  wgmma_rs64(acc, h[8], h[9], h[10], h[11], blo + 256);
  wgmma_rs64(acc, h[12], h[13], h[14], h[15], blo + 384);
}
template <bool INIT>
__device__ __forceinline__ void g2_h(float (&acc)[32], const uint32_t (&h)[16], uint32_t blo) {
  if (INIT) wgmma_rs64_init(acc, h[0], h[1], h[2], h[3], blo);
  else      wgmma_rs64(acc, h[0], h[1], h[2], h[3], blo);
  wgmma_rs64(acc, h[4], h[5], h[6], h[7], blo + 128);
  wgmma_rs64(acc, h[8], h[9], h[10], h[11], blo + 256);
  wgmma_rs64(acc, h[12], h[13], h[14], h[15], blo + 384);
}
__device__ __forceinline__ void g2_o(float (&acc)[32], const uint32_t (&o)[20], uint32_t blo) {
#pragma unroll
  for (int s = 0; s < 5; s++) wgmma_rs64(acc, o[4 * s], o[4 * s + 1], o[4 * s + 2], o[4 * s + 3], blo + 1536 + 128 * s);
}
__device__ __forceinline__ uint4 pack8(const float (&acc)[32], int v) {
  return make_uint4(pack_bf16(acc[8 * v + 0], acc[8 * v + 1]), pack_bf16(acc[8 * v + 2], acc[8 * v + 3]),
                    pack_bf16(acc[8 * v + 4], acc[8 * v + 5]), pack_bf16(acc[8 * v + 6], acc[8 * v + 7]));
}
__device__ __forceinline__ uint32_t add_bf16x2(uint32_t a, uint32_t b) {
  uint32_t r;
  asm("add.rn.bf16x2 %0, %1, %2;" : "=r"(r) : "r"(a), "r"(b));
  return r;
}
__device__ __forceinline__ void store_tile(const uint4 (&f)[4], uint32_t ta, uint32_t tx) {
#pragma unroll
  for (int v = 0; v < 4; v++) stsm4(ta + (((2 * v) ^ tx) << 4), f[v]);
}

__global__ void __launch_bounds__(NTHREADS, 1)
fused_kernel(const __grid_constant__ CUtensorMap tmX, const __grid_constant__ CUtensorMap tmQA,
             const __grid_constant__ CUtensorMap tmQB, const __grid_constant__ CUtensorMap tmW1,
             const __grid_constant__ CUtensorMap tmW3, const __grid_constant__ CUtensorMap tmW2,
             const __grid_constant__ CUtensorMap tmWo, const __grid_constant__ CUtensorMap tmOut, const Params prm) {
  extern __shared__ __align__(1024) uint8_t smem_raw[];
  const uint32_t sb = smem_u32(smem_raw);
  const uint32_t bar0 = sb + SM_BAR;
  const int tid = threadIdx.x;
  const int warp = __shfl_sync(0xffffffffu, tid >> 5, 0);
  const int lane = tid & 31;
  const int j = blockIdx.x & 7, mt = blockIdx.x >> 3;
#define BAR(i) (bar0 + 8 * (i))

  if (warp >= 4) {
    asm volatile("setmaxnreg.inc.sync.aligned.u32 224;");
    const int w = (warp >> 2) - 1;
    const int tau = tid & 127;
    const int g = lane >> 2, t = lane & 3;
    const int half0 = 64 * mt + 16 * (warp & 3);
    const bool elect = tau == 0;
    const uint32_t xlo = (((sb + SM_X + w * 8192) & 0x3FFFFu) >> 4) | (1u << 16);
    const uint32_t ringq = (((sb + SM_RING) & 0x3FFFFu) >> 4) | (256u << 16);
    const uint32_t ringr = (((sb + SM_RING + 12288) & 0x3FFFFu) >> 4) | (64u << 16);
    const uint32_t ringg = (((sb + SM_RING) & 0x3FFFFu) >> 4) | (512u << 16);

    if (elect && w == 0) TSTAMP(6);
    float accm[96], accr[24];
#pragma unroll
    for (int i = 0; i < 96; i++) accm[i] = 0.f;
#pragma unroll
    for (int i = 0; i < 24; i++) accr[i] = 0.f;
    fence_regs(accm); fence_regs(accr);
    asm volatile("bar.sync 0, 384;" ::: "memory");
    asm volatile("barrier.cluster.arrive.relaxed.aligned;" ::: "memory");
#pragma unroll 1
    for (int ks = 0; ks < 20; ks++) {
      const int s = ks & 3;
      if ((ks & 1) == 0) mbar_wait(BAR(B_XFULL + (ks >> 1)), 0);
      mbar_wait(BAR(B_FULL + s), (ks >> 2) & 1);
      if (ks == 0 && elect && w == 0) TSTAMP(24);
      wg_fence();
      const uint32_t a = xlo + (ks >> 1) * 1024 + (ks & 1) * 4, b = ringq + s * 1024, br = ringr + s * 1024;
      wgmma_ss192(accm, a, b);
      wgmma_ss48r(accr, a, br);
      wgmma_ss192(accm, a + 2, b + 128);
      wgmma_ss48r(accr, a + 2, br + 32);
      wg_commit();
      wg_wait<1>();
      if (ks > 0 && elect) mbar_arrive(BAR(B_EMPTYQ + ((ks - 1) & 3)));
    }
    if (elect && w == 0) TSTAMP(25);
    asm volatile("barrier.cluster.wait.acquire.aligned;" ::: "memory");

    float accA[64], accB[64];
    uint32_t h0[16], h1[16], h2[16], of[20];
    AttnOps ao;

    uint32_t zero;
    asm volatile("mov.b32 %0, 0;" : "=r"(zero));
#define GU_STAGE0(ACC, G, FIRST)                                                       \
    {                                                                                  \
      mbar_wait(BAR(B_FULL + ((G) & 3)), ((G) >> 2) & 1);                              \
      wg_fence();                                                                      \
      const uint32_t a = xlo + (((G) - 20) % 10) * 1024, b = ringg + ((G) & 3) * 1024; \
      if ((FIRST) == 1) wgmma_ss128_init(ACC, a, b);                                   \
      else if ((FIRST) == 2) wgmma_ss128_sc(ACC, a, b, zero);                          \
      else wgmma_ss128(ACC, a, b);                                                     \
      wgmma_ss128(ACC, a + 2, b + 128);                                                \
      wgmma_ss128(ACC, a + 4, b + 256);                                                \
      wgmma_ss128(ACC, a + 6, b + 384);                                                \
      wg_commit();                                                                     \
    }
#define GU_REL(G)                                                                      \
    {                                                                                  \
      wg_wait<1>();                                                                    \
      if (elect) mbar_arrive(BAR(((G) <= 40 ? B_EMPTYQ : B_EMPTY) + (((G) - 1) & 3))); \
      if (elect) TSTAMP(64 + 32 * w + (G) - 20);                                       \
    }
#define GU_STAGE(ACC, G, FIRST) GU_STAGE0(ACC, G, FIRST) GU_REL(G)
#define PIN2(A, B) { const uint32_t z_ = __float_as_uint(pin(0.f, prm.zero)); A = __uint_as_float(__float_as_uint(A) ^ z_); B = __uint_as_float(__float_as_uint(B) ^ z_); }

    GU_STAGE(accA, 20, 1)
    fence_regs(accm); fence_regs(accr);
    GU_STAGE(accA, 21, 0)
    GU_STAGE(accA, 22, 0)
    mbar_wait(BAR(B_EPI), 0);
    const uint32_t st_addr = sb + SM_CSB + (2 * (16 * (warp & 3) + g) + w) * 8;
    float2 s1 = lds64f(st_addr), s2 = lds64f(st_addr + 128);
    const uint32_t tag = __float_as_uint(s1.x) & 1u;
    const uint32_t csA = sb + SM_CSA + t * 8;
    uint4* halo = g_halo + ((j * 2 + w) * 64 + 4 * mt + (warp & 3)) * 160 + lane;
    CS ca, cb;
#define K_LOAD(R, B) R = qkv_cs<1, B>(csA);
#define V_LOAD(R, B) R = qkv_cs<2, B>(csA);
#define Q_LOAD(R, B) R = qkv_cs<0, B>(csA);
#define K_PIECE(R, B) qkv_piece<1, B>(accm, accr, s1, s2, R, ao.k[1][B], ao.k[2][B]);
#define V_PIECE(R, B) qkv_piece<2, B>(accm, accr, s1, s2, R, ao.v[1][B], ao.v[2][B]); ao.v[2][B].x = movm(ao.v[2][B].x); ao.v[2][B].y = movm(ao.v[2][B].y);
#define V_MOVM(B) ao.v[1][B].x = movm(ao.v[1][B].x); ao.v[1][B].y = movm(ao.v[1][B].y);
#define Q_PIECE(R, B) q_piece<B>(accm, accr, s1.y, s2.y, R, ao.q1[B], ao.q2[B]);
    K_LOAD(ca, 0)
    K_PIECE(ca, 0)
    ao.k[2][0].x = set_tag(ao.k[2][0].x, tag);
    V_LOAD(ca, 0) K_LOAD(cb, 1)
    GU_STAGE(accA, 23, 0)
    PIN2(s1.y, s2.y) V_PIECE(ca, 0) K_PIECE(cb, 1)
    ao.k[2][1].x = set_tag(ao.k[2][1].x, tag); ao.k[2][1].y = set_tag(ao.k[2][1].y, tag);
    V_LOAD(ca, 1) K_LOAD(cb, 2)
    GU_STAGE(accA, 24, 0)
    PIN2(s1.y, s2.y) V_PIECE(ca, 1) K_PIECE(cb, 2)
    ao.k[2][2].y = set_tag(ao.k[2][2].y, tag);
    st_tagged(halo, make_uint4(set_tag(ao.v[2][0].x, tag), ao.v[2][0].y, set_tag(ao.v[2][1].x, tag), ao.v[2][1].y));
    st_tagged(halo + 32, make_uint4(ao.k[2][0].x, ao.k[2][0].y, ao.k[2][1].y, ao.k[2][2].x));
    V_LOAD(ca, 2) K_LOAD(cb, 3)
    GU_STAGE(accA, 25, 0)
    PIN2(s1.y, s2.y) V_PIECE(ca, 2) K_PIECE(cb, 3)
    V_LOAD(ca, 3) K_LOAD(cb, 4)
    GU_STAGE(accA, 26, 0)
    PIN2(s1.y, s2.y) V_PIECE(ca, 3) K_PIECE(cb, 4)
    ao.k[2][4].x = set_tag(ao.k[2][4].x, tag);
    st_tagged(halo + 64, make_uint4(set_tag(ao.v[2][2].x, tag), ao.v[2][2].y, set_tag(ao.v[2][3].x, tag), ao.v[2][3].y));
    st_tagged(halo + 128, make_uint4(ao.k[2][2].y, ao.k[2][3].x, ao.k[2][4].x, ao.k[2][4].y));
    V_LOAD(ca, 4) Q_LOAD(cb, 0)
    GU_STAGE(accA, 27, 0)
    PIN2(s1.y, s2.y) V_PIECE(ca, 4)
    st_tagged(halo + 96, make_uint4(ao.k[2][1].x, ao.k[2][3].y, set_tag(ao.v[2][4].x, tag), ao.v[2][4].y));
    Q_PIECE(cb, 0)
    Q_LOAD(ca, 1) Q_LOAD(cb, 2)
    GU_STAGE(accA, 28, 0)
    PIN2(s1.y, s2.y) Q_PIECE(ca, 1) Q_PIECE(cb, 2) V_MOVM(0) V_MOVM(1)
    Q_LOAD(ca, 3) Q_LOAD(cb, 4)
    const bool first = half0 == 0;
    const uint4* const hsrc = (first ? halo : halo - 160) + (HALO_DEP & prm.zero);
    uint64_t hv[10];
    halo_load(hv, hsrc);
    GU_STAGE(accA, 29, 0)
    PIN2(s1.y, s2.y) Q_PIECE(ca, 3) Q_PIECE(cb, 4) V_MOVM(2) V_MOVM(3) V_MOVM(4)
    __syncwarp();
    if (lane == 0) mbar_arrive(BAR(B_CSFREE));
    wg_wait<0>();
    fence_regs(accA);
    if (elect) mbar_arrive(BAR(B_EMPTYQ + 1));
    if (elect && w == 0) TSTAMP(26);
    mbar_wait(BAR(B_EPI), 0);
    {
      float4 sc[4];
      {
        const uint32_t mlo = t < 2 ? 0xffffffffu : 0u;
        const bool p0 = 2 * t > g, p1 = 2 * t + 1 > g;
        sc[0] = attn_own<0>(ao, mlo, p0, p1); sc[1] = attn_own<1>(ao, mlo, p0, p1);
        sc[2] = attn_own<2>(ao, mlo, p0, p1); sc[3] = attn_own<3>(ao, mlo, p0, p1);
      }
      const uint32_t tz = tag ^ __float_as_uint(pin(0.f, prm.zero)) ^ (__float_as_uint(sc[3].w) & prm.zero);
      uint32_t it = 0;
#pragma unroll 1
      while (__any_sync(0xffffffffu, halo_bad(hv, tz) & 1u) && ++it < SPIN_LIMIT) halo_reload(hv, hsrc);
#define HLO(i) ((uint32_t)hv[i])
#define HHI(i) ((uint32_t)(hv[i] >> 32))
      ao.v[0][0] = make_uint2(HLO(0), HHI(0)); ao.v[0][1] = make_uint2(HLO(1), HHI(1));
      ao.v[0][2] = make_uint2(HLO(4), HHI(4)); ao.v[0][3] = make_uint2(HLO(5), HHI(5));
      ao.v[0][4] = make_uint2(HLO(7), HHI(7));
      ao.k[0][0] = make_uint2(HLO(2), HHI(2)); ao.k[0][1] = make_uint2(HLO(6), HLO(3));
      ao.k[0][2] = make_uint2(HHI(3), HLO(8)); ao.k[0][3] = make_uint2(HHI(8), HHI(6));
      ao.k[0][4] = make_uint2(HLO(9), HHI(9));
      attn_compute(ao, sc, first, g, t, s1.x, s2.x, of);
    }
    if (elect && w == 0) TSTAMP(22);

    float3 e1 = make_float3(0.5f * s1.x, s1.y, 0.5f * s1.x * s1.x);
    float3 e2 = make_float3(0.5f * s2.x, s2.y, 0.5f * s2.x * s2.x);
    const uint32_t csC = sb + SM_CSC + t * 8, csB = sb + SM_CSB + t * 8;
    GU_STAGE0(accB, 30, 1)
    mbar_wait(BAR(B_GU + 0), 0);
#define GU_PIECE(ACC, N, CSADDR, H) PIN2(e1.y, e2.y) GU_PIECE0(ACC, N, CSADDR, H)
#define GU_PIECE0(ACC, N, CSADDR, H) gu_piece<N>(ACC, e1, e2, ca, H); if ((N) < 7) ca = gu_cs<((N) < 7 ? (N) + 1 : 7)>(CSADDR);
    ca = gu_cs<0>(csC);
    GU_PIECE(accA, 0, csC, h0)
    GU_STAGE(accB, 31, 0) GU_PIECE(accA, 1, csC, h0)
    GU_STAGE(accB, 32, 0) GU_PIECE(accA, 2, csC, h0)
    GU_STAGE(accB, 33, 0) GU_PIECE(accA, 3, csC, h0)
    GU_STAGE(accB, 34, 0) GU_PIECE(accA, 4, csC, h0)
    GU_STAGE(accB, 35, 0) GU_PIECE(accA, 5, csC, h0)
    GU_STAGE(accB, 36, 0) GU_PIECE(accA, 6, csC, h0)
    GU_STAGE(accB, 37, 0) GU_PIECE(accA, 7, csC, h0)
    GU_STAGE(accB, 38, 0)
    GU_STAGE(accB, 39, 0)
    if (elect && w == 0) TSTAMP(27);

    float (&accC)[64] = accA;
    GU_STAGE(accC, 40, 2)
    fence_regs(accB);
    GU_STAGE(accC, 41, 0)
    GU_STAGE(accC, 42, 0)
    mbar_wait(BAR(B_GU + 1), 0);
    ca = gu_cs<0>(csB);
    GU_PIECE(accB, 0, csB, h1)
    GU_STAGE(accC, 43, 0) GU_PIECE(accB, 1, csB, h1)
    GU_STAGE(accC, 44, 0) GU_PIECE(accB, 2, csB, h1)
    GU_STAGE(accC, 45, 0) GU_PIECE(accB, 3, csB, h1)
    GU_STAGE(accC, 46, 0) GU_PIECE(accB, 4, csB, h1)
    GU_STAGE(accC, 47, 0) GU_PIECE(accB, 5, csB, h1)
    const int rho = j & 1;
    const uint32_t peer_bar0 = mapa(bar0, rho ^ 1);
    GU_STAGE(accC, 48, 0)
    if (elect) mbar_arrive_remote(peer_bar0 + 8 * B_REMPTY);
    GU_PIECE(accB, 6, csB, h1)
    GU_STAGE(accC, 49, 0)
    GU_PIECE(accB, 7, csB, h1)
    if (elect && w == 0) TSTAMP(28);

    float acc0[32], acc1[32];
    const uint32_t cdesc = ((sb & 0x3FFFFu) >> 4) | (1u << 16);
    constexpr uint32_t CS16 = CSLOT >> 4;

    const uint32_t csA2 = sb + SM_CSA + t * 8;
    mbar_wait(BAR(B_CFULL + 0), 0);
    wg_fence();
    g2_h<true>(acc0, h0, cdesc);
    g2_h<false>(acc0, h1, cdesc + 512);
    wg_commit();
    wg_wait<1>();
    if (elect) mbar_arrive(BAR(B_EMPTY + 1));
    fence_regs(accC);
    mbar_wait(BAR(B_GU + 2), 0);
    ca = gu_cs<0>(csA2);
    GU_PIECE0(accC, 0, csA2, h2) GU_PIECE0(accC, 1, csA2, h2)
    wg_fence();
    g2_o(acc0, of, cdesc);
    wgmma_rs64(acc0, h2[0], h2[1], h2[2], h2[3], cdesc + 1024);
    wg_commit();
    GU_PIECE0(accC, 2, csA2, h2) GU_PIECE0(accC, 3, csA2, h2) GU_PIECE0(accC, 4, csA2, h2) GU_PIECE0(accC, 5, csA2, h2)
    wg_fence();
    wgmma_rs64(acc0, h2[4], h2[5], h2[6], h2[7], cdesc + 1024 + 128);
    wgmma_rs64(acc0, h2[8], h2[9], h2[10], h2[11], cdesc + 1024 + 256);
    wg_commit();
    GU_PIECE0(accC, 6, csA2, h2) GU_PIECE0(accC, 7, csA2, h2)
    wg_fence();
    wgmma_rs64(acc0, h2[12], h2[13], h2[14], h2[15], cdesc + 1024 + 384);
    wg_commit();
    if (elect && w == 0) TSTAMP(29);

    const bool keeper = (w == rho);
    const uint32_t wofs = (warp & 3) * 2048;
    const uint32_t rbuf = sb + SM_RECV + wofs;
    const uint32_t peer_buf = mapa(rbuf, rho ^ 1) + lane * 16;
    const int trow = (lane & 7) + (lane & 8);
    const uint32_t tofs = trow * 128, tx = (lane >> 4) ^ (trow & 7);
    uint4 kp[4];
#define DBG2(C, K)
#define RBUF(K) (rbuf + ((K) & 3) * 8192)
#define PACK(ACC) { kp[0] = pack8(ACC, 0); kp[1] = pack8(ACC, 1); kp[2] = pack8(ACC, 2); kp[3] = pack8(ACC, 3); }
#define KEEP_LOAD(K)                                                                             \
      {                                                                                          \
        _Pragma("unroll")                                                                        \
        for (int v = 0; v < 4; v++) ku[v] = lds128(RBUF(K) + v * 512 + lane * 16);               \
      }
#define KEEP_TILE(K)                                                                             \
      {                                                                                          \
        _Pragma("unroll")                                                                        \
        for (int v = 0; v < 4; v++)                                                              \
          kp[v] = make_uint4(add_bf16x2(kp[v].x, ku[v].x), add_bf16x2(kp[v].y, ku[v].y), add_bf16x2(kp[v].z, ku[v].z), add_bf16x2(kp[v].w, ku[v].w)); \
        __syncwarp();                                                                            \
        store_tile(kp, RBUF(K) + tofs, tx);                                                      \
      }
#define KEEP_OUT(K)                                                                              \
      {                                                                                          \
        fence_async_smem();                                                                      \
        __syncwarp();                                                                            \
        if (elect_one()) { tma_add3d(&tmOut, RBUF(K), 64 * (K), half0, w); bulk_commit(); }      \
      }
#define SEND(ACC, K)                                                                             \
      {                                                                                          \
        _Pragma("unroll")                                                                        \
        for (int v = 0; v < 4; v++) st_async(peer_buf + ((K) & 3) * 8192 + v * 512, pack8(ACC, v), peer_bar0 + 8 * (B_RFULL + (K))); \
      }
#define RLAG 2
#define G2_CHUNK(CUR, PREV, C)                                                                   \
      {                                                                                          \
        const int s_ = (C) < 5 ? (C) : (C) - 5;                                                  \
        const uint32_t bl = cdesc + s_ * CS16;                                                   \
        DBG2(C, 0)                                                                               \
        const bool okx = keeper ? ((C) < 2 || mbar_test(BAR(B_RFULL + (C) - 2), 0))              \
                                : (((C) - 1 < RLAG && (C) > 1) || mbar_test(BAR(B_REMPTY + (C) - 1), 0)); \
        wg_fence();                                                                              \
        g2_h<true>(CUR, h0, bl);                                                                 \
        g2_h<false>(CUR, h1, bl + 512);                                                          \
        wg_commit();                                                                             \
        DBG2(C, 1)                                                                               \
        wg_wait<1>();                                                                            \
        DBG2(C, 2)                                                                               \
        if ((C) - 1 < 5 && elect) mbar_arrive(BAR(B_CEMPTY + (C) - 1));                          \
        fence_regs(PREV);                                                                        \
        if (keeper) {                                                                            \
          if ((C) >= 2) {                                                                        \
            uint4 ku[4];                                                                         \
            if (!okx) mbar_wait(BAR(B_RFULL + (C) - 2), 0);                                      \
            KEEP_LOAD((C) - 2)                                                                   \
              \
            if ((C) - 2 + RLAG < 9 && elect_one()) { bulk_wait_read<1>(); mbar_arrive_remote(peer_bar0 + 8 * (B_REMPTY + (C) - 2 + RLAG)); } \
            KEEP_TILE((C) - 2)                                                                   \
          }                                                                                      \
        } else {                                                                                 \
          if (!okx) mbar_wait(BAR(B_REMPTY + (C) - 1), 0);         \
          SEND(PREV, (C) - 1)                                                                    \
        }                                                                                        \
        DBG2(C, 4)                                                                               \
        wg_fence();                                                                              \
        g2_o(CUR, of, bl);                                                                       \
        g2_h<false>(CUR, h2, bl + 1024);                                                         \
        wg_commit();                                                                             \
        DBG2(C, 5)                                                                               \
        const int n_ = (C) + 1 < 5 ? (C) + 1 : (C) - 4;                                          \
        const bool okc = (C) == 9 || mbar_test(BAR(B_CFULL + n_), (C) + 1 < 5 ? 0 : 1);          \
        if (keeper) {                                                                            \
          if ((C) >= 2) {                                                                        \
            if ((C) == 2) mbar_wait(BAR(B_INIT), 0);                \
            KEEP_OUT((C) - 2)                                                                    \
          }                                                                                      \
          PACK(PREV)                                                                             \
        }                                                                                        \
        if (!okc) mbar_wait(BAR(B_CFULL + n_), (C) + 1 < 5 ? 0 : 1);                             \
        DBG2(C, 6)                                                                               \
      }                                                                                          \
      if (elect && w == 0) TSTAMP(32 + 3 * ((C) - 1));
    mbar_wait(BAR(B_CFULL + 1), 0);
    G2_CHUNK(acc1, acc0, 1) G2_CHUNK(acc0, acc1, 2) G2_CHUNK(acc1, acc0, 3) G2_CHUNK(acc0, acc1, 4)
    G2_CHUNK(acc1, acc0, 5) G2_CHUNK(acc0, acc1, 6) G2_CHUNK(acc1, acc0, 7) G2_CHUNK(acc0, acc1, 8)
    G2_CHUNK(acc1, acc0, 9)
    if (keeper) {
      uint4 ku[4];
      mbar_wait(BAR(B_RFULL + 8), 0);
      KEEP_LOAD(8)
      KEEP_TILE(8)
      KEEP_OUT(8)
    }
    wg_wait<0>();
    fence_regs(acc1);
    if (elect && w == 0) TSTAMP(30);
    {
      PACK(acc1)
      const uint32_t b_ = sb + SM_LAST + w * 8192 + wofs;
      store_tile(kp, b_ + tofs, tx);
      fence_async_smem();
      __syncwarp();
      if (elect_one()) { tma_add3d(&tmOut, b_, 64 * 9, half0, w); bulk_commit(); bulk_wait_read<0>(); }
      if (elect) { TSTAMP(31); GSTAMP(63); }
      if (elect && !keeper) atomicAdd(&g_done[0], 1u);
    }
    } else {
    asm volatile("setmaxnreg.dec.sync.aligned.u32 56;");
    if (warp == 0) {
      if (elect_one()) {
        prefetch_tmap(&tmX); prefetch_tmap(&tmQA); prefetch_tmap(&tmQB);
#pragma unroll
        for (int i = 0; i < 3; i++) mbar_init(BAR(B_XFULL + i), 1);
#pragma unroll
        for (int i = 0; i < 4; i++) mbar_init(BAR(B_FULL + i), 1);
        asm volatile("fence.mbarrier_init.release.cluster;" ::: "memory");
#pragma unroll
        for (int ks = 0; ks < 4; ks++) {
          if ((ks & 1) == 0) {
            mbar_expect_tx(BAR(B_XFULL + (ks >> 1)), SLOT);
            tma3d(sb + SM_X + (ks >> 1) * SLOT, &tmX, 32 * ks, 64 * mt, 0, BAR(B_XFULL + (ks >> 1)));
            tma3d(sb + SM_X + (ks >> 1) * SLOT + 8192, &tmX, 32 * ks, 64 * mt, 1, BAR(B_XFULL + (ks >> 1)));
          }
          mbar_expect_tx(BAR(B_FULL + ks), QBYTES);
          tma3d(sb + SM_RING + ks * SLOT, &tmQA, 80 * j, 32 * ks, 0, BAR(B_FULL + ks));
          tma3d(sb + SM_RING + ks * SLOT + 12288, &tmQB, 80 * j + 64, 32 * ks, 0, BAR(B_FULL + ks));
        }
        mbar_expect_tx(BAR(B_XFULL + 2), SLOT);
        tma3d(sb + SM_X + 2 * SLOT, &tmX, 128, 64 * mt, 0, BAR(B_XFULL + 2));
        tma3d(sb + SM_X + 2 * SLOT + 8192, &tmX, 128, 64 * mt, 1, BAR(B_XFULL + 2));
        TSTAMP(5);
      }
      __syncwarp();
    } else if (warp == 1) {
      const int r = 128 * mt + 16 * j + (lane & 15);
      const __nv_bfloat16* p = prm.x + (size_t)r * D_ + 64 * (lane >> 4);
      asm volatile("prefetch.global.L2 [%0];" ::"l"(p));
    } else if (warp == 2) {
      const int r = 4 * mt + (lane >> 3), u = lane & 7;
      const __nv_bfloat16* p = prm.wqkv + (size_t)r * NQKV + 640 * (u >> 1) + 80 * j + 64 * (u & 1);
      if (u < 6) asm volatile("prefetch.global.L2 [%0];" ::"l"(p));
    } else if (warp == 3) {
      if (elect_one()) {
#pragma unroll
        for (int i = 3; i < B_COUNT; i++) {
          if (i >= B_FULL && i < B_EMPTY) continue;
          const uint32_t cnt = (i >= B_EMPTY && i < B_CFULL) ? 2u : (i >= B_CEMPTY && i < B_EPI) ? 2u : (i == B_REMPTY) ? 2u
                             : (i == B_CSFREE) ? 8u : (i >= B_EMPTYQ && i < B_XFREE) ? 3u : (i > B_INIT && i < B_EMPTYQ) ? 4u : 1u;
          mbar_init(BAR(i), cnt);
        }
#pragma unroll
        for (int i = 0; i < 9; i++) mbar_expect_tx(BAR(B_RFULL + i), 8192);
        asm volatile("fence.mbarrier_init.release.cluster;" ::: "memory");
      }
      __syncwarp();
    }
    asm volatile("bar.sync 0, 384;" ::: "memory");
    asm volatile("barrier.cluster.arrive.relaxed.aligned;" ::: "memory");
    const uint32_t ring = sb + SM_RING;
    if (warp == 0) {
      asm volatile("barrier.cluster.wait.acquire.aligned;" ::: "memory");
      if (elect_one()) {
        prefetch_tmap(&tmW1); prefetch_tmap(&tmW3); prefetch_tmap(&tmW2); prefetch_tmap(&tmWo); prefetch_tmap(&tmOut);
#pragma unroll 1
        for (int ks = 4; ks < 20; ks++) {
          if ((ks & 1) == 0 && ks < 18) {
            const int c = (ks >> 1) + 1;
            mbar_expect_tx(BAR(B_XFULL + c), SLOT);
            tma3d_mc(sb + SM_X + c * SLOT + (j & 1) * 8192, &tmX, 64 * c, 64 * mt, j & 1, BAR(B_XFULL + c));
          }
          const int s = ks & 3;
          mbar_wait(BAR(B_EMPTYQ + s), ((ks >> 2) & 1) ^ 1);
          mbar_expect_tx(BAR(B_FULL + s), QBYTES);
          tma3d(ring + s * SLOT, &tmQA, 80 * j, 32 * ks, 0, BAR(B_FULL + s));
          tma3d(ring + s * SLOT + 12288, &tmQB, 80 * j + 64, 32 * ks, 0, BAR(B_FULL + s));
        }
        TSTAMP(1);
#pragma unroll 1
        for (int g = 20; g < 50; g++) {
          const int s = g & 3, i = (g - 20) / 10, ks = (g - 20) - 10 * i;
          if (g < 44) mbar_wait(BAR(B_EMPTYQ + s), ((g >> 2) & 1) ^ 1);
          else        mbar_wait(BAR(B_EMPTY + s), (g >> 2) == 12);
          mbar_expect_tx(BAR(B_FULL + s), SLOT);
          tma2d(ring + s * SLOT, &tmW1, 192 * j + 64 * i, 64 * ks, BAR(B_FULL + s));
          tma2d(ring + s * SLOT + 8192, &tmW3, 192 * j + 64 * i, 64 * ks, BAR(B_FULL + s));
          if (g == W0_AT) {
            mbar_wait(BAR(B_XFREE), 0);
            mbar_expect_tx(BAR(B_CFULL), CSLOT);
            tma2d(sb + 24576, &tmWo, 0, 80 * j, BAR(B_CFULL));
          }
          if (g > W0_AT) tma2d(sb + 8192 * (g - W0_AT - 1), &tmW2, 0, 192 * j + 64 * (g - W0_AT - 1), BAR(B_CFULL));
        }
        TSTAMP(2);
#pragma unroll
        for (int q = 49 - W0_AT; q < 3; q++) tma2d(sb + 8192 * q, &tmW2, 0, 192 * j + 64 * q, BAR(B_CFULL));
#pragma unroll 1
        for (int c = 1; c < 10; c++) {
          if (c == 2) mbar_wait(BAR(B_EMPTY + 2), 1);
          if (c == 3) mbar_wait(BAR(B_EMPTY + 0), 0);
          if (c == 4) mbar_wait(BAR(B_EMPTY + 1), 0);
          const int s = c < 5 ? c : c - 5;
          if (c >= 5) mbar_wait(BAR(B_CEMPTY + s), 0);
          const uint32_t dst = sb + s * CSLOT;
          mbar_expect_tx(BAR(B_CFULL + s), CSLOT);
#pragma unroll
          for (int q = 0; q < 3; q++) tma2d(dst + 8192 * q, &tmW2, 64 * c, 192 * j + 64 * q, BAR(B_CFULL + s));
          tma2d(dst + 24576, &tmWo, 64 * c, 80 * j, BAR(B_CFULL + s));
        }
        TSTAMP(3);
      }
    } else {
      uint32_t tag = 0;
      if (warp != 2) tag = launch_tag();
      if (warp == 3) {
        if (lane == 0) { asm volatile("st.shared.b32 [%0], %1;" ::"r"(sb + SM_TAG), "r"(tag) : "memory"); mbar_arrive(BAR(B_TAG)); }
        float* const gd = g_cs + j * 4 * 512;
        if (lane < 16 && mt < 15) st_tagged32(gd + 16 * mt + lane, tag ^ 1u);
        if (lane < 16) st_tagged32(gd + 512 * (1 + (lane >> 3)) + 8 * mt + (lane & 7), tag ^ 1u);
      }
      if (warp == 1) {
        const int par = lane >> 4, hf = (lane >> 3) & 1, il = lane & 7;
        const uint32_t a0 = sb + SM_X + par * 8192 + (8 * j + il) * 128;
        if (hf == 0) st_tagged64(&g_stats[128 * mt + 2 * (8 * j + il) + par], tag ^ 1u, 0u);
#pragma unroll
        for (int u = 0; u < 10; u++)
          st_tagged(g_halo + ((j * 2 + u / 5) * 64 + 4 * mt + 3) * 160 + 32 * (u % 5) + lane, make_uint4(tag ^ 1u, 0u, tag ^ 1u, 0u));
        if (lane == 0) TSTAMP(15);
        mbar_wait(BAR(B_XFULL), 0);
        if (lane == 0) TSTAMP(7);
        const float c = bf_lo(lds32(a0 + il * 16));
        float s0 = 0.f, q0 = 0.f, s1 = 0.f, q1 = 0.f;
#pragma unroll 1
        for (int ch = 0; ch < 10; ch++) {
          mbar_wait(BAR(B_XFULL + ch), 0);
          const uint32_t a = a0 + ch * SLOT;
          const uint4 v0 = lds128(a + (((4 * hf + 0) ^ il) << 4)), v1 = lds128(a + (((4 * hf + 1) ^ il) << 4));
          const uint4 v2 = lds128(a + (((4 * hf + 2) ^ il) << 4)), v3 = lds128(a + (((4 * hf + 3) ^ il) << 4));
          stat8(v0, c, s0, q0); stat8(v1, c, s1, q1); stat8(v2, c, s0, q0); stat8(v3, c, s1, q1);
        }
        s0 += s1; q0 += q1;
        s0 += __shfl_xor_sync(0xffffffffu, s0, 8); q0 += __shfl_xor_sync(0xffffffffu, q0, 8);
        const float m = s0 * (1.0f / D_);
        const float var = fmaxf(fmaf(-m, m, q0 * (1.0f / D_)), 0.f);
        const float r = rsqrtf(var + 1e-5f);
        if (hf == 0) st_tagged64(&g_stats[128 * mt + 2 * (8 * j + il) + par], set_tag(__float_as_uint(r), tag), __float_as_uint(-(c + m)));
        __syncwarp();
        if (lane == 0) { mbar_arrive(BAR(B_PUB)); TSTAMP(8); }
      }
      float* const gdst = g_cs + j * 4 * 512;
      if (warp == 2) {
        int g = 0;
#pragma unroll 1
        for (int rnd = 0; rnd < 3; rnd++) {
          uint32_t off, step;
          if (rnd == 0) {
            const int blk = min(mt, 14), cq = lane & 3, rq = lane >> 2;
            if (blk < 12) {
              const int r = 2 * (rq & 3) + (rq >> 2);
              off = (blk >> 2) * 4096 + r * 128 + (((2 * (blk & 3) + (cq >> 1)) ^ r) << 4) + (cq & 1) * 8;
              step = 1024;
            } else {
              off = 12288 + (blk - 12) * 1024 + rq * 32 + (((cq >> 1) ^ (rq >> 2)) << 4) + (cq & 1) * 8;
              step = 256;
            }
          } else {
            const int r = (lane >> 1) & 7, hi = lane >> 4;
            off = (mt >> 3) * 8192 + (r + 8 * hi) * 128 + (((mt & 7) ^ r) << 4) + (lane & 1) * 8;
            step = 2048;
          }
          float a0 = 0.f, a1 = 0.f, a2 = 0.f, a3 = 0.f;
          const int gend = 20 + 10 * rnd;
#pragma unroll 1
          for (; g < gend; g++) {
            const int s = g & 3;
            mbar_wait(BAR(B_FULL + s), (g >> 2) & 1);
            const uint32_t p = ring + s * SLOT + off;
            uint2 v[4];
#pragma unroll
            for (int i = 0; i < 4; i++) v[i] = lds64u(p + i * step);
            __syncwarp();
            if (lane == 0) mbar_arrive(BAR(B_EMPTYQ + s));
            if (g == 8) { mbar_wait(BAR(B_TAG), 0); tag = lds32(sb + SM_TAG); }
#pragma unroll
            for (int i = 0; i < 4; i++) { a0 += bf_lo(v[i].x); a1 += bf_hi(v[i].x); a2 += bf_lo(v[i].y); a3 += bf_hi(v[i].y); }
          }
          const bool u4 = lane & 16, u3 = lane & 8;
          const float b0 = (u4 ? a2 : a0) + __shfl_xor_sync(0xffffffffu, u4 ? a0 : a2, 16);
          const float b1 = (u4 ? a3 : a1) + __shfl_xor_sync(0xffffffffu, u4 ? a1 : a3, 16);
          float v = (u3 ? b1 : b0) + __shfl_xor_sync(0xffffffffu, u3 ? b0 : b1, 8);
          v += __shfl_xor_sync(0xffffffffu, v, 4);
          if (rnd > 0) v += __shfl_xor_sync(0xffffffffu, v, 2);
          const int cs_ = 2 * (lane >> 4) + ((lane >> 3) & 1);
          if (rnd == 0) { if (!(lane & 4) && mt < 15) st_tagged32(gdst + 16 * mt + 4 * (lane & 3) + cs_, set_tag(__float_as_uint(v), tag)); }
          else          { if (!(lane & 6)) st_tagged32(gdst + 512 * rnd + 8 * mt + 4 * (lane & 1) + cs_, set_tag(__float_as_uint(v), tag)); }
          __syncwarp();
          if (lane == 0) { mbar_arrive(BAR(rnd == 0 ? B_PUBQ : B_PUB + rnd)); TSTAMP(rnd == 0 ? 14 : 15 + rnd); }
        }
      }
      if (warp == 1) {
        const int gofs = 512 * 3 + 256 * (mt & 1) + 64 * (mt >> 3) + 16 * ((mt >> 1) & 3);
        if (!(lane & 2)) st_tagged32(gdst + gofs + col_of_lane(lane), tag ^ 1u);
        mbar_wait(BAR(B_CSFREE), 0);
        if (elect_one()) {
#pragma unroll 1
          for (int u = 0; u < (j < 2 ? 16 : 8); u++) {
            const int ch = j + (u & 8);
            tma_store3d(&tmOut, sb + SM_X + ch * SLOT + (u & 7) * 2048, 64 * ch, 64 * mt + 16 * (u & 3), (u >> 2) & 1);
          }
          bulk_commit();
          asm volatile("cp.async.bulk.wait_group 0;" ::: "memory");
          mbar_arrive(BAR(B_XFREE));
          fence_async();
          asm volatile("st.release.gpu.global.u32 [%0], %1;" ::"l"(&g_init[mt * 8 + j]), "r"(tag) : "memory");
          TSTAMP(13);
        }
        __syncwarp();
        const char* p = reinterpret_cast<const char*>(((mt >> 3) ? prm.w3 : prm.w1) + (size_t)(320 * (mt & 1) + (lane >> 1)) * F_ + 8 * (lane & 1) +
                                                      192 * j + 128 + 16 * ((mt >> 1) & 3));
        float a[16];
        col_task(a, p, 16 * F_ * 2);
        treduce<8, 16>(a, lane); treduce<4, 8>(a, lane); treduce<2, 4>(a, lane);
        const float v = a[0] + __shfl_xor_sync(0xffffffffu, a[0], 2);
        if (!(lane & 2)) st_tagged32(gdst + gofs + col_of_lane(lane), set_tag(__float_as_uint(v), tag));
        __syncwarp();
        if (lane == 0) { mbar_arrive(BAR(B_PUB + 3)); TSTAMP(18); }
      }
      if (warp == 3) {
        const uint4* cs = reinterpret_cast<const uint4*>(g_cs + j * 4 * 512);
        {
          mbar_wait(BAR(B_PUB), 0);
          const uint4* st = reinterpret_cast<const uint4*>(g_stats + 128 * mt);
          uint4 u0, u1;
          uint32_t it = 0;
#pragma unroll 1
          while (true) {
            u0 = ld_tagged(st + lane); u1 = ld_tagged(st + lane + 32);
            if (!__any_sync(0xffffffffu, ((u0.x ^ tag) | (u0.z ^ tag) | (u1.x ^ tag) | (u1.z ^ tag)) & 1u) || ++it > SPIN_LIMIT) break;
          }
          sts128(sb + SM_CSB + lane * 16, u0); sts128(sb + SM_CSB + (lane + 32) * 16, u1);
          const int l2 = min(lane + 32, 59);
          mbar_wait(BAR(B_PUBQ), 0);
          it = 0;
#pragma unroll 1
          while (true) {
            u0 = ld_tagged(cs + lane); u1 = ld_tagged(cs + l2);
            if (!__any_sync(0xffffffffu, (tagbad4(u0, tag) | tagbad4(u1, tag)) & 1u) || ++it > SPIN_LIMIT) break;
          }
          sts128(sb + SM_CSA + lane * 16, u0); sts128(sb + SM_CSA + l2 * 16, u1);
          __syncwarp();
          if (lane == 0) { mbar_arrive(BAR(B_EPI)); TSTAMP(9); }
        }
#pragma unroll 1
        for (int rnd = 1; rnd < 4; rnd++) {
          mbar_wait(BAR(B_PUB + rnd), 0);
          if (rnd == 2) mbar_wait(BAR(B_CSFREE), 0);
          uint4 u0, u1;
          uint32_t it = 0;
#pragma unroll 1
          while (true) {
            u0 = ld_tagged(cs + 128 * rnd + lane);
            u1 = u0;
            if (rnd == 3) u1 = ld_tagged(cs + 128 * rnd + 64 + lane);
            if (!__any_sync(0xffffffffu, (tagbad4(u0, tag) | tagbad4(u1, tag)) & 1u) || ++it > SPIN_LIMIT) break;
          }
          if (rnd == 3) u0 = fadd4(u0, u1);
          sts128(sb + (rnd == 1 ? SM_CSC : rnd == 2 ? SM_CSB : SM_CSA) + lane * 16, u0);
          __syncwarp();
          if (lane == 0) { mbar_arrive(BAR(B_GU + rnd - 1)); TSTAMP(19 + rnd - 1); }
        }
        {
          uint32_t it = 0;
#pragma unroll 1
          while (true) {
            unsigned v;
            asm volatile("ld.acquire.gpu.global.u32 %0, [%1];" : "=r"(v) : "l"(&g_init[mt * 8 + (lane & 7)]) : "memory");
            if (!__any_sync(0xffffffffu, (v ^ tag) & 1u) || ++it > SPIN_LIMIT) break;
          }
          __syncwarp();
          if (lane == 0) mbar_arrive(BAR(B_INIT));
        }
      }
    }
    __syncwarp();
    if (warp != 0) asm volatile("barrier.cluster.wait.acquire.aligned;" ::: "memory");
  }
#undef BAR
}

typedef CUresult (*EncodeFn)(CUtensorMap*, CUtensorMapDataType, cuuint32_t, void*, const cuuint64_t*, const cuuint64_t*,
                             const cuuint32_t*, const cuuint32_t*, CUtensorMapInterleave, CUtensorMapSwizzle,
                             CUtensorMapL2promotion, CUtensorMapFloatOOBfill);

CUtensorMap make_map(EncodeFn enc, const void* base, int rank, const cuuint64_t* dims, const cuuint64_t* strides, const cuuint32_t* box,
                     CUtensorMapSwizzle sw = CU_TENSOR_MAP_SWIZZLE_128B) {
  CUtensorMap m;
  const cuuint32_t es[3] = {1, 1, 1};
  enc(&m, CU_TENSOR_MAP_DATA_TYPE_BFLOAT16, (cuuint32_t)rank, const_cast<void*>(base), dims, strides, box, es,
      CU_TENSOR_MAP_INTERLEAVE_NONE, sw, CU_TENSOR_MAP_L2_PROMOTION_L2_128B, CU_TENSOR_MAP_FLOAT_OOB_FILL_NONE);
  return m;
}

}

extern "C" void kernel_launch(void* const* d_in, const int* in_sizes, int n_in, void* d_out, int out_size) {
  (void)in_sizes; (void)n_in; (void)out_size;
  static EncodeFn enc = nullptr;
  if (!enc) {
    void* fn = nullptr;
    cudaDriverEntryPointQueryResult q;
    cudaGetDriverEntryPoint("cuTensorMapEncodeTiled", &fn, cudaEnableDefault, &q);
    enc = (EncodeFn)fn;
    cudaFuncSetAttribute(fused_kernel, cudaFuncAttributeMaxDynamicSharedMemorySize, SM_TOTAL);
  }
  Params p;
  p.x = (const __nv_bfloat16*)d_in[0];
  p.wqkv = (const __nv_bfloat16*)d_in[1];
  p.w1 = (const __nv_bfloat16*)d_in[4];
  p.w3 = (const __nv_bfloat16*)d_in[5];
  p.out = (__nv_bfloat16*)d_out;
  p.zero = 0;
  const void* wo = d_in[2];
  const void* w2 = d_in[6];

  CUtensorMap tmX, tmQA, tmQB, tmW1, tmW3, tmW2, tmWo, tmOut;
  { const cuuint64_t d[3] = {D_, S_ / 2, 2}, s[2] = {D_ * 4, D_ * 2}; const cuuint32_t b[3] = {64, 64, 1}; tmX = make_map(enc, p.x, 3, d, s, b); }
  { const cuuint64_t d[3] = {D_, S_ / 2, 2}, s[2] = {D_ * 4, D_ * 2}; const cuuint32_t b[3] = {64, 16, 1}; tmOut = make_map(enc, p.out, 3, d, s, b); }
  { const cuuint64_t d[3] = {D_, D_, 3}, s[2] = {NQKV * 2, D_ * 2};
    const cuuint32_t b[3] = {64, 32, 3}; tmQA = make_map(enc, p.wqkv, 3, d, s, b);
    const cuuint32_t b2[3] = {16, 32, 3}; tmQB = make_map(enc, p.wqkv, 3, d, s, b2, CU_TENSOR_MAP_SWIZZLE_32B); }
  { const cuuint64_t d[2] = {F_, D_}, s[1] = {F_ * 2}; const cuuint32_t b[2] = {64, 64}; tmW1 = make_map(enc, p.w1, 2, d, s, b); tmW3 = make_map(enc, p.w3, 2, d, s, b); }
  { const cuuint64_t d[2] = {D_, F_}, s[1] = {D_ * 2}; const cuuint32_t b[2] = {64, 64}; tmW2 = make_map(enc, w2, 2, d, s, b); }
  { const cuuint64_t d[2] = {D_, D_}, s[1] = {D_ * 2}; const cuuint32_t b[2] = {64, 80}; tmWo = make_map(enc, wo, 2, d, s, b); }

  cudaLaunchConfig_t cfg = {};
  cfg.gridDim = dim3(128);
  cfg.blockDim = dim3(NTHREADS);
  cfg.dynamicSmemBytes = SM_TOTAL;
  cfg.stream = cudaStreamPerThread;
  cudaLaunchAttribute at[1];
  at[0].id = cudaLaunchAttributeClusterDimension;
  at[0].val.clusterDim.x = 2; at[0].val.clusterDim.y = 1; at[0].val.clusterDim.z = 1;
  cfg.attrs = at; cfg.numAttrs = 1;
  cudaLaunchKernelEx(&cfg, fused_kernel, tmX, tmQA, tmQB, tmW1, tmW3, tmW2, tmWo, tmOut, p);
}
```

```cpp
#include <cuda_runtime.h>
#include <cuda_bf16.h>
#include <cuda.h>
#include <stdint.h>

namespace {

constexpr int S_ = 2048, D_ = 640, F_ = 1536, NQKV = 1920;
constexpr int NTHREADS = 384;

constexpr int SM_X    = 0;
constexpr int SM_RING = 163840;
constexpr int SLOT    = 16384;
constexpr int QBYTES  = 15360;
constexpr int CSLOT   = 34816;
constexpr int SM_RECV = 196608;
constexpr int SM_LAST = 174080;
constexpr int SM_CSA  = 229376;
constexpr int SM_CSB  = SM_CSA + 960;
constexpr int SM_CSC  = SM_CSB + 1024;
constexpr int SM_BAR  = 231872;
constexpr int SM_TAG  = SM_BAR + 568;
constexpr int SM_TOTAL = 232448;
constexpr int B_XFULL = 0, B_FULL = 10, B_EMPTY = 14, B_CFULL = 18, B_CEMPTY = 23, B_EPI = 28, B_GU = 29, B_PUB = 32,
              B_RFULL = 36, B_CSFREE = 45, B_REMPTY = 46, B_INIT = 47, B_EMPTYQ = 57, B_XFREE = 61, B_PUBQ = 62, B_TAG = 63, B_COUNT = 64;

constexpr int W0_AT = 46;
constexpr uint32_t SPIN_LIMIT = 1u << 17;
constexpr uint32_t DESC_HI   = 0x40000040u;
constexpr uint32_t DESC_HI32 = 0xC0000010u;

__device__ uint4  g_halo[8 * 2 * 64 * 5 * 32];
__device__ unsigned g_init[16 * 8];
__device__ float2 g_stats[S_];
__device__ float  g_cs[8 * 4 * 512];
__device__ unsigned g_done[32];
#define TSTAMP(id) do {} while (0)
#define GSTAMP(id) do {} while (0)
#define TVALUE(id, v) do { (void)(v); } while (0)

struct Params {
  const __nv_bfloat16* x;
  const __nv_bfloat16* wqkv;
  const __nv_bfloat16* w1;
  const __nv_bfloat16* w3;
  __nv_bfloat16* out;
  uint32_t zero;
};

__device__ __forceinline__ uint32_t smem_u32(const void* p) { return (uint32_t)__cvta_generic_to_shared(p); }
__device__ __forceinline__ bool elect_one() {
  uint32_t p;
  asm volatile("{\n.reg .pred P;\nelect.sync _|P, 0xffffffff;\nselp.u32 %0, 1, 0, P;\n}" : "=r"(p));
  return p != 0;
}
__device__ __forceinline__ void mbar_init(uint32_t bar, uint32_t cnt) {
  asm volatile("mbarrier.init.shared::cta.b64 [%0], %1;" ::"r"(bar), "r"(cnt) : "memory");
}
__device__ __forceinline__ void mbar_expect_tx(uint32_t bar, uint32_t bytes) {
  asm volatile("mbarrier.arrive.expect_tx.shared::cta.b64 _, [%0], %1;" ::"r"(bar), "r"(bytes) : "memory");
}
__device__ __forceinline__ void mbar_arrive(uint32_t bar) {
  asm volatile("mbarrier.arrive.shared::cta.b64 _, [%0];" ::"r"(bar) : "memory");
}
__device__ __forceinline__ bool mbar_try(uint32_t bar, uint32_t parity) {
  uint32_t ok;
  asm volatile("{\n.reg .pred p;\nmbarrier.try_wait.parity.shared::cta.b64 p, [%1], %2;\nselp.u32 %0, 1, 0, p;\n}"
               : "=r"(ok) : "r"(bar), "r"(parity) : "memory");
  return ok != 0;
}
__device__ __forceinline__ void mbar_wait(uint32_t bar, uint32_t parity) {
  uint32_t it = 0;
#pragma unroll 1
  while (!mbar_try(bar, parity)) { if (++it > SPIN_LIMIT) break; }
}
__device__ __forceinline__ bool mbar_test(uint32_t bar, uint32_t parity) {
  uint32_t ok;
  asm volatile("{\n.reg .pred p;\nmbarrier.test_wait.parity.shared::cta.b64 p, [%1], %2;\nselp.u32 %0, 1, 0, p;\n}"
               : "=r"(ok) : "r"(bar), "r"(parity) : "memory");
  return ok != 0;
}
__device__ __forceinline__ void tma2d(uint32_t dst, const CUtensorMap* m, int c0, int c1, uint32_t bar) {
  asm volatile("cp.async.bulk.tensor.2d.shared::cluster.global.mbarrier::complete_tx::bytes [%0], [%1, {%3, %4}], [%2];"
               ::"r"(dst), "l"(m), "r"(bar), "r"(c0), "r"(c1) : "memory");
}
__device__ __forceinline__ void tma3d(uint32_t dst, const CUtensorMap* m, int c0, int c1, int c2, uint32_t bar) {
  asm volatile("cp.async.bulk.tensor.3d.shared::cluster.global.mbarrier::complete_tx::bytes [%0], [%1, {%3, %4, %5}], [%2];"
               ::"r"(dst), "l"(m), "r"(bar), "r"(c0), "r"(c1), "r"(c2) : "memory");
}
__device__ __forceinline__ void tma3d_mc(uint32_t dst, const CUtensorMap* m, int c0, int c1, int c2, uint32_t bar) {
  asm volatile("cp.async.bulk.tensor.3d.shared::cluster.global.mbarrier::complete_tx::bytes.multicast::cluster [%0], [%1, {%3, %4, %5}], [%2], %6;"
               ::"r"(dst), "l"(m), "r"(bar), "r"(c0), "r"(c1), "r"(c2), "h"((uint16_t)3) : "memory");
}
__device__ __forceinline__ void tma_store3d(const CUtensorMap* m, uint32_t src, int c0, int c1, int c2) {
  asm volatile("cp.async.bulk.tensor.3d.global.shared::cta.tile.bulk_group [%0, {%2, %3, %4}], [%1];"
               ::"l"(m), "r"(src), "r"(c0), "r"(c1), "r"(c2) : "memory");
}
__device__ __forceinline__ void tma_add3d(const CUtensorMap* m, uint32_t src, int c0, int c1, int c2) {
  asm volatile("cp.reduce.async.bulk.tensor.3d.global.shared::cta.add.tile.bulk_group [%0, {%2, %3, %4}], [%1];"
               ::"l"(m), "r"(src), "r"(c0), "r"(c1), "r"(c2) : "memory");
}
__device__ __forceinline__ void bulk_commit() { asm volatile("cp.async.bulk.commit_group;" ::: "memory"); }
template <int N> __device__ __forceinline__ void bulk_wait_read() { asm volatile("cp.async.bulk.wait_group.read %0;" ::"n"(N) : "memory"); }
__device__ __forceinline__ void fence_async() { asm volatile("fence.proxy.async;" ::: "memory"); }
__device__ __forceinline__ void fence_async_smem() { asm volatile("fence.proxy.async.shared::cta;" ::: "memory"); }
__device__ __forceinline__ void stsm4(uint32_t addr, const uint4 v) {
  asm volatile("stmatrix.sync.aligned.m8n8.x4.shared.b16 [%0], {%1, %2, %3, %4};" ::"r"(addr), "r"(v.x), "r"(v.y), "r"(v.z), "r"(v.w) : "memory");
}
__device__ __forceinline__ void prefetch_tmap(const CUtensorMap* m) {
  asm volatile("prefetch.tensormap [%0];" ::"l"(m) : "memory");
}
__device__ __forceinline__ void wg_fence() { asm volatile("wgmma.fence.sync.aligned;" ::: "memory"); }
__device__ __forceinline__ void wg_commit() { asm volatile("wgmma.commit_group.sync.aligned;" ::: "memory"); }
template <int N> __device__ __forceinline__ void wg_wait() { asm volatile("wgmma.wait_group.sync.aligned %0;" ::"n"(N) : "memory"); }
template <int N> __device__ __forceinline__ void fence_regs(float (&a)[N]) {
#pragma unroll
  for (int i = 0; i < N; i++) asm volatile("" : "+f"(a[i]) :: "memory");
}
__device__ __forceinline__ uint32_t pack_bf16(float lo, float hi) {
  uint32_t r;
  asm("cvt.rn.bf16x2.f32 %0, %1, %2;" : "=r"(r) : "f"(hi), "f"(lo));
  return r;
}
__device__ __forceinline__ float bf_lo(uint32_t w) { return __uint_as_float(w << 16); }
__device__ __forceinline__ float bf_hi(uint32_t w) { return __uint_as_float(w & 0xffff0000u); }
__device__ __forceinline__ float2 lds64f(uint32_t addr) {
  float2 v;
  asm volatile("ld.shared.v2.f32 {%0, %1}, [%2];" : "=f"(v.x), "=f"(v.y) : "r"(addr));
  return v;
}
__device__ __forceinline__ uint2 lds64u(uint32_t addr) {
  uint2 v;
  asm volatile("ld.shared.v2.b32 {%0, %1}, [%2];" : "=r"(v.x), "=r"(v.y) : "r"(addr) : "memory");
  return v;
}
__device__ __forceinline__ uint32_t lds32(uint32_t addr) {
  uint32_t v;
  asm volatile("ld.shared.b32 %0, [%1];" : "=r"(v) : "r"(addr) : "memory");
  return v;
}
__device__ __forceinline__ uint4 lds128(uint32_t addr) {
  uint4 v;
  asm volatile("ld.shared.v4.b32 {%0, %1, %2, %3}, [%4];" : "=r"(v.x), "=r"(v.y), "=r"(v.z), "=r"(v.w) : "r"(addr) : "memory");
  return v;
}
__device__ __forceinline__ void sts128(uint32_t addr, uint4 v) {
  asm volatile("st.shared.v4.b32 [%0], {%1, %2, %3, %4};" ::"r"(addr), "r"(v.x), "r"(v.y), "r"(v.z), "r"(v.w) : "memory");
}
__device__ __forceinline__ float ex2f(float x) { float y; asm("ex2.approx.ftz.f32 %0, %1;" : "=f"(y) : "f"(x)); return y; }
__device__ __forceinline__ float rcpf(float x) { float y; asm("rcp.approx.ftz.f32 %0, %1;" : "=f"(y) : "f"(x)); return y; }
__device__ __forceinline__ void mma16816_c(float (&d)[4], uint32_t a0, uint32_t a1, uint32_t a2, uint32_t a3, uint32_t b0, uint32_t b1, float ci) {
  asm volatile("mma.sync.aligned.m16n8k16.row.col.f32.bf16.bf16.f32 {%0,%1,%2,%3}, {%4,%5,%6,%7}, {%8,%9}, {%10,%10,%10,%10};"
               : "=f"(d[0]), "=f"(d[1]), "=f"(d[2]), "=f"(d[3]) : "r"(a0), "r"(a1), "r"(a2), "r"(a3), "r"(b0), "r"(b1), "f"(ci));
}
__device__ __forceinline__ void mma1688(float (&c)[4], uint32_t a0, uint32_t a1, uint32_t b0) {
  asm volatile("mma.sync.aligned.m16n8k8.row.col.f32.bf16.bf16.f32 {%0,%1,%2,%3}, {%4,%5}, {%6}, {%0,%1,%2,%3};"
               : "+f"(c[0]), "+f"(c[1]), "+f"(c[2]), "+f"(c[3]) : "r"(a0), "r"(a1), "r"(b0));
}
__device__ __forceinline__ uint32_t movm(uint32_t a) {
  uint32_t d;
  asm volatile("movmatrix.sync.aligned.m8n8.trans.b16 %0, %1;" : "=r"(d) : "r"(a));
  return d;
}
__device__ __forceinline__ uint32_t mapa(uint32_t addr, uint32_t rank) {
  uint32_t r;
  asm("mapa.shared::cluster.u32 %0, %1, %2;" : "=r"(r) : "r"(addr), "r"(rank));
  return r;
}
__device__ __forceinline__ void mbar_arrive_remote(uint32_t cluster_addr) {
  asm volatile("mbarrier.arrive.shared::cluster.b64 _, [%0];" ::"r"(cluster_addr) : "memory");
}
__device__ __forceinline__ void st_async(uint32_t cluster_addr, uint4 v, uint32_t cluster_bar) {
  asm volatile("st.async.weak.shared::cluster.mbarrier::complete_tx::bytes.v4.b32 [%0], {%1, %2, %3, %4}, [%5];"
               ::"r"(cluster_addr), "r"(v.x), "r"(v.y), "r"(v.z), "r"(v.w), "r"(cluster_bar) : "memory");
}
__device__ __forceinline__ void st_tagged(void* p, uint4 v) {
  asm volatile("{\n.reg .b128 r;\nmov.b128 r, {%1, %2};\nst.relaxed.gpu.global.b128 [%0], r;\n}"
               ::"l"(p), "l"(((uint64_t)v.y << 32) | v.x), "l"(((uint64_t)v.w << 32) | v.z) : "memory");
}
__device__ __forceinline__ uint4 ld_tagged(const void* p) {
  uint64_t a, b;
  asm volatile("{\n.reg .b128 r;\nld.relaxed.gpu.global.b128 r, [%2];\nmov.b128 {%0, %1}, r;\n}" : "=l"(a), "=l"(b) : "l"(p) : "memory");
  return make_uint4((uint32_t)a, (uint32_t)(a >> 32), (uint32_t)b, (uint32_t)(b >> 32));
}
__device__ __forceinline__ void st_tagged64(void* p, uint32_t x, uint32_t y) {
  asm volatile("st.relaxed.gpu.global.b64 [%0], %1;" ::"l"(p), "l"(((uint64_t)y << 32) | x) : "memory");
}
__device__ __forceinline__ void st_tagged32(void* p, uint32_t x) {
  asm volatile("st.relaxed.gpu.global.b32 [%0], %1;" ::"l"(p), "r"(x) : "memory");
}
__device__ __forceinline__ uint32_t set_tag(uint32_t w, uint32_t tag) { return (w & 0xfffffffeu) | tag; }
__device__ __forceinline__ uint32_t launch_tag() {
  unsigned v;
  asm volatile("ld.relaxed.gpu.global.u32 %0, [%1];" : "=r"(v) : "l"(&g_done[0]) : "memory");
  return ((v >> 7) + 1) & 1u;
}

__device__ __forceinline__ void wgmma_rs192(float (&d)[96], uint32_t a0, uint32_t a1, uint32_t a2, uint32_t a3, uint32_t blo) {
  asm volatile("{\n.reg .pred p;\n.reg .b64 db;\n"
    "setp.eq.b32 p, 0, 0;\n"
    "mov.b64 db, {%100, %101};\n"
    "wgmma.mma_async.sync.aligned.m64n192k16.f32.bf16.bf16 {%0, %1, %2, %3, %4, %5, %6, %7, %8, %9, %10, %11, %12, %13, %14, %15, %16, %17, %18, %19, %20, %21, %22, %23, %24, %25, %26, %27, %28, %29, %30, %31, %32, %33, %34, %35, %36, %37, %38, %39, %40, %41, %42, %43, %44, %45, %46, %47, %48, %49, %50, %51, %52, %53, %54, %55, %56, %57, %58, %59, %60, %61, %62, %63, %64, %65, %66, %67, %68, %69, %70, %71, %72, %73, %74, %75, %76, %77, %78, %79, %80, %81, %82, %83, %84, %85, %86, %87, %88, %89, %90, %91, %92, %93, %94, %95}, {%96,%97,%98,%99}, db, p, 1, 1, 1;\n}\n"
    :
        "+f"(d[0]), "+f"(d[1]), "+f"(d[2]), "+f"(d[3]), "+f"(d[4]), "+f"(d[5]), "+f"(d[6]), "+f"(d[7]),
        "+f"(d[8]), "+f"(d[9]), "+f"(d[10]), "+f"(d[11]), "+f"(d[12]), "+f"(d[13]), "+f"(d[14]), "+f"(d[15]),
        "+f"(d[16]), "+f"(d[17]), "+f"(d[18]), "+f"(d[19]), "+f"(d[20]), "+f"(d[21]), "+f"(d[22]), "+f"(d[23]),
        "+f"(d[24]), "+f"(d[25]), "+f"(d[26]), "+f"(d[27]), "+f"(d[28]), "+f"(d[29]), "+f"(d[30]), "+f"(d[31]),
        "+f"(d[32]), "+f"(d[33]), "+f"(d[34]), "+f"(d[35]), "+f"(d[36]), "+f"(d[37]), "+f"(d[38]), "+f"(d[39]),
        "+f"(d[40]), "+f"(d[41]), "+f"(d[42]), "+f"(d[43]), "+f"(d[44]), "+f"(d[45]), "+f"(d[46]), "+f"(d[47]),
        "+f"(d[48]), "+f"(d[49]), "+f"(d[50]), "+f"(d[51]), "+f"(d[52]), "+f"(d[53]), "+f"(d[54]), "+f"(d[55]),
        "+f"(d[56]), "+f"(d[57]), "+f"(d[58]), "+f"(d[59]), "+f"(d[60]), "+f"(d[61]), "+f"(d[62]), "+f"(d[63]),
        "+f"(d[64]), "+f"(d[65]), "+f"(d[66]), "+f"(d[67]), "+f"(d[68]), "+f"(d[69]), "+f"(d[70]), "+f"(d[71]),
        "+f"(d[72]), "+f"(d[73]), "+f"(d[74]), "+f"(d[75]), "+f"(d[76]), "+f"(d[77]), "+f"(d[78]), "+f"(d[79]),
        "+f"(d[80]), "+f"(d[81]), "+f"(d[82]), "+f"(d[83]), "+f"(d[84]), "+f"(d[85]), "+f"(d[86]), "+f"(d[87]),
        "+f"(d[88]), "+f"(d[89]), "+f"(d[90]), "+f"(d[91]), "+f"(d[92]), "+f"(d[93]), "+f"(d[94]), "+f"(d[95])
    : "r"(a0), "r"(a1), "r"(a2), "r"(a3), "r"(blo), "n"(DESC_HI));
}
__device__ __forceinline__ void wgmma_rs48r(float (&d)[24], uint32_t a0, uint32_t a1, uint32_t a2, uint32_t a3, uint32_t blo) {
  asm volatile("{\n.reg .pred p;\n.reg .b64 db;\n"
    "setp.eq.b32 p, 0, 0;\n"
    "mov.b64 db, {%28, %29};\n"
    "wgmma.mma_async.sync.aligned.m64n48k16.f32.bf16.bf16 {%0, %1, %2, %3, %4, %5, %6, %7, %8, %9, %10, %11, %12, %13, %14, %15, %16, %17, %18, %19, %20, %21, %22, %23}, {%24,%25,%26,%27}, db, p, 1, 1, 1;\n}\n"
    :
        "+f"(d[0]), "+f"(d[1]), "+f"(d[2]), "+f"(d[3]), "+f"(d[4]), "+f"(d[5]), "+f"(d[6]), "+f"(d[7]),
        "+f"(d[8]), "+f"(d[9]), "+f"(d[10]), "+f"(d[11]), "+f"(d[12]), "+f"(d[13]), "+f"(d[14]), "+f"(d[15]),
        "+f"(d[16]), "+f"(d[17]), "+f"(d[18]), "+f"(d[19]), "+f"(d[20]), "+f"(d[21]), "+f"(d[22]), "+f"(d[23])
    : "r"(a0), "r"(a1), "r"(a2), "r"(a3), "r"(blo), "n"(DESC_HI32));
}
__device__ __forceinline__ void wgmma_ss128_init(float (&d)[64], uint32_t alo, uint32_t blo) {
  asm volatile("{\n.reg .pred p;\n.reg .b64 da, db;\n"
    "setp.ne.b32 p, 0, 0;\n"
    "mov.b64 da, {%64, %66};\nmov.b64 db, {%65, %66};\n"
    "wgmma.mma_async.sync.aligned.m64n128k16.f32.bf16.bf16 {%0, %1, %2, %3, %4, %5, %6, %7, %8, %9, %10, %11, %12, %13, %14, %15, %16, %17, %18, %19, %20, %21, %22, %23, %24, %25, %26, %27, %28, %29, %30, %31, %32, %33, %34, %35, %36, %37, %38, %39, %40, %41, %42, %43, %44, %45, %46, %47, %48, %49, %50, %51, %52, %53, %54, %55, %56, %57, %58, %59, %60, %61, %62, %63}, da, db, p, 1, 1, 0, 1;\n}\n"
    :
        "=f"(d[0]), "=f"(d[1]), "=f"(d[2]), "=f"(d[3]), "=f"(d[4]), "=f"(d[5]), "=f"(d[6]), "=f"(d[7]),
        "=f"(d[8]), "=f"(d[9]), "=f"(d[10]), "=f"(d[11]), "=f"(d[12]), "=f"(d[13]), "=f"(d[14]), "=f"(d[15]),
        "=f"(d[16]), "=f"(d[17]), "=f"(d[18]), "=f"(d[19]), "=f"(d[20]), "=f"(d[21]), "=f"(d[22]), "=f"(d[23]),
        "=f"(d[24]), "=f"(d[25]), "=f"(d[26]), "=f"(d[27]), "=f"(d[28]), "=f"(d[29]), "=f"(d[30]), "=f"(d[31]),
        "=f"(d[32]), "=f"(d[33]), "=f"(d[34]), "=f"(d[35]), "=f"(d[36]), "=f"(d[37]), "=f"(d[38]), "=f"(d[39]),
        "=f"(d[40]), "=f"(d[41]), "=f"(d[42]), "=f"(d[43]), "=f"(d[44]), "=f"(d[45]), "=f"(d[46]), "=f"(d[47]),
        "=f"(d[48]), "=f"(d[49]), "=f"(d[50]), "=f"(d[51]), "=f"(d[52]), "=f"(d[53]), "=f"(d[54]), "=f"(d[55]),
        "=f"(d[56]), "=f"(d[57]), "=f"(d[58]), "=f"(d[59]), "=f"(d[60]), "=f"(d[61]), "=f"(d[62]), "=f"(d[63])
    : "r"(alo), "r"(blo), "n"(DESC_HI));
}
__device__ __forceinline__ void wgmma_ss128_sc(float (&d)[64], uint32_t alo, uint32_t blo, uint32_t sc) {
  asm volatile("{\n.reg .pred p;\n.reg .b64 da, db;\n"
    "setp.ne.b32 p, %67, 0;\n"
    "mov.b64 da, {%64, %66};\nmov.b64 db, {%65, %66};\n"
    "wgmma.mma_async.sync.aligned.m64n128k16.f32.bf16.bf16 {%0, %1, %2, %3, %4, %5, %6, %7, %8, %9, %10, %11, %12, %13, %14, %15, %16, %17, %18, %19, %20, %21, %22, %23, %24, %25, %26, %27, %28, %29, %30, %31, %32, %33, %34, %35, %36, %37, %38, %39, %40, %41, %42, %43, %44, %45, %46, %47, %48, %49, %50, %51, %52, %53, %54, %55, %56, %57, %58, %59, %60, %61, %62, %63}, da, db, p, 1, 1, 0, 1;\n}\n"
    :
        "+f"(d[0]), "+f"(d[1]), "+f"(d[2]), "+f"(d[3]), "+f"(d[4]), "+f"(d[5]), "+f"(d[6]), "+f"(d[7]),
        "+f"(d[8]), "+f"(d[9]), "+f"(d[10]), "+f"(d[11]), "+f"(d[12]), "+f"(d[13]), "+f"(d[14]), "+f"(d[15]),
        "+f"(d[16]), "+f"(d[17]), "+f"(d[18]), "+f"(d[19]), "+f"(d[20]), "+f"(d[21]), "+f"(d[22]), "+f"(d[23]),
        "+f"(d[24]), "+f"(d[25]), "+f"(d[26]), "+f"(d[27]), "+f"(d[28]), "+f"(d[29]), "+f"(d[30]), "+f"(d[31]),
        "+f"(d[32]), "+f"(d[33]), "+f"(d[34]), "+f"(d[35]), "+f"(d[36]), "+f"(d[37]), "+f"(d[38]), "+f"(d[39]),
        "+f"(d[40]), "+f"(d[41]), "+f"(d[42]), "+f"(d[43]), "+f"(d[44]), "+f"(d[45]), "+f"(d[46]), "+f"(d[47]),
        "+f"(d[48]), "+f"(d[49]), "+f"(d[50]), "+f"(d[51]), "+f"(d[52]), "+f"(d[53]), "+f"(d[54]), "+f"(d[55]),
        "+f"(d[56]), "+f"(d[57]), "+f"(d[58]), "+f"(d[59]), "+f"(d[60]), "+f"(d[61]), "+f"(d[62]), "+f"(d[63])
    : "r"(alo), "r"(blo), "n"(DESC_HI), "r"(sc));
}
__device__ __forceinline__ void wgmma_ss128(float (&d)[64], uint32_t alo, uint32_t blo) {
  asm volatile("{\n.reg .pred p;\n.reg .b64 da, db;\n"
    "setp.eq.b32 p, 0, 0;\n"
    "mov.b64 da, {%64, %66};\nmov.b64 db, {%65, %67};\n"
    "wgmma.mma_async.sync.aligned.m64n128k16.f32.bf16.bf16 {%0, %1, %2, %3, %4, %5, %6, %7, %8, %9, %10, %11, %12, %13, %14, %15, %16, %17, %18, %19, %20, %21, %22, %23, %24, %25, %26, %27, %28, %29, %30, %31, %32, %33, %34, %35, %36, %37, %38, %39, %40, %41, %42, %43, %44, %45, %46, %47, %48, %49, %50, %51, %52, %53, %54, %55, %56, %57, %58, %59, %60, %61, %62, %63}, da, db, p, 1, 1, 0, 1;\n}\n"
    :
        "+f"(d[0]), "+f"(d[1]), "+f"(d[2]), "+f"(d[3]), "+f"(d[4]), "+f"(d[5]), "+f"(d[6]), "+f"(d[7]),
        "+f"(d[8]), "+f"(d[9]), "+f"(d[10]), "+f"(d[11]), "+f"(d[12]), "+f"(d[13]), "+f"(d[14]), "+f"(d[15]),
        "+f"(d[16]), "+f"(d[17]), "+f"(d[18]), "+f"(d[19]), "+f"(d[20]), "+f"(d[21]), "+f"(d[22]), "+f"(d[23]),
        "+f"(d[24]), "+f"(d[25]), "+f"(d[26]), "+f"(d[27]), "+f"(d[28]), "+f"(d[29]), "+f"(d[30]), "+f"(d[31]),
        "+f"(d[32]), "+f"(d[33]), "+f"(d[34]), "+f"(d[35]), "+f"(d[36]), "+f"(d[37]), "+f"(d[38]), "+f"(d[39]),
        "+f"(d[40]), "+f"(d[41]), "+f"(d[42]), "+f"(d[43]), "+f"(d[44]), "+f"(d[45]), "+f"(d[46]), "+f"(d[47]),
        "+f"(d[48]), "+f"(d[49]), "+f"(d[50]), "+f"(d[51]), "+f"(d[52]), "+f"(d[53]), "+f"(d[54]), "+f"(d[55]),
        "+f"(d[56]), "+f"(d[57]), "+f"(d[58]), "+f"(d[59]), "+f"(d[60]), "+f"(d[61]), "+f"(d[62]), "+f"(d[63])
    : "r"(alo), "r"(blo), "n"(DESC_HI), "n"(DESC_HI));
}
__device__ __forceinline__ void wgmma_rs64_init(float (&d)[32], uint32_t a0, uint32_t a1, uint32_t a2, uint32_t a3, uint32_t blo) {
  asm volatile("{\n.reg .pred p;\n.reg .b64 db;\n"
    "setp.ne.b32 p, 0, 0;\n"
    "mov.b64 db, {%36, %37};\n"
    "wgmma.mma_async.sync.aligned.m64n64k16.f32.bf16.bf16 {%0, %1, %2, %3, %4, %5, %6, %7, %8, %9, %10, %11, %12, %13, %14, %15, %16, %17, %18, %19, %20, %21, %22, %23, %24, %25, %26, %27, %28, %29, %30, %31}, {%32,%33,%34,%35}, db, p, 1, 1, 1;\n}\n"
    :
        "=f"(d[0]), "=f"(d[1]), "=f"(d[2]), "=f"(d[3]), "=f"(d[4]), "=f"(d[5]), "=f"(d[6]), "=f"(d[7]),
        "=f"(d[8]), "=f"(d[9]), "=f"(d[10]), "=f"(d[11]), "=f"(d[12]), "=f"(d[13]), "=f"(d[14]), "=f"(d[15]),
        "=f"(d[16]), "=f"(d[17]), "=f"(d[18]), "=f"(d[19]), "=f"(d[20]), "=f"(d[21]), "=f"(d[22]), "=f"(d[23]),
        "=f"(d[24]), "=f"(d[25]), "=f"(d[26]), "=f"(d[27]), "=f"(d[28]), "=f"(d[29]), "=f"(d[30]), "=f"(d[31])
    : "r"(a0), "r"(a1), "r"(a2), "r"(a3), "r"(blo), "n"(DESC_HI));
}
__device__ __forceinline__ void wgmma_rs64(float (&d)[32], uint32_t a0, uint32_t a1, uint32_t a2, uint32_t a3, uint32_t blo) {
  asm volatile("{\n.reg .pred p;\n.reg .b64 db;\n"
    "setp.eq.b32 p, 0, 0;\n"
    "mov.b64 db, {%36, %37};\n"
    "wgmma.mma_async.sync.aligned.m64n64k16.f32.bf16.bf16 {%0, %1, %2, %3, %4, %5, %6, %7, %8, %9, %10, %11, %12, %13, %14, %15, %16, %17, %18, %19, %20, %21, %22, %23, %24, %25, %26, %27, %28, %29, %30, %31}, {%32,%33,%34,%35}, db, p, 1, 1, 1;\n}\n"
    :
        "+f"(d[0]), "+f"(d[1]), "+f"(d[2]), "+f"(d[3]), "+f"(d[4]), "+f"(d[5]), "+f"(d[6]), "+f"(d[7]),
        "+f"(d[8]), "+f"(d[9]), "+f"(d[10]), "+f"(d[11]), "+f"(d[12]), "+f"(d[13]), "+f"(d[14]), "+f"(d[15]),
        "+f"(d[16]), "+f"(d[17]), "+f"(d[18]), "+f"(d[19]), "+f"(d[20]), "+f"(d[21]), "+f"(d[22]), "+f"(d[23]),
        "+f"(d[24]), "+f"(d[25]), "+f"(d[26]), "+f"(d[27]), "+f"(d[28]), "+f"(d[29]), "+f"(d[30]), "+f"(d[31])
    : "r"(a0), "r"(a1), "r"(a2), "r"(a3), "r"(blo), "n"(DESC_HI));
}

__device__ __forceinline__ float pin(float x, uint32_t zero) {
  uint32_t c;
  asm volatile("mov.u32 %0, %%clock;" : "=r"(c) :: "memory");
  return __uint_as_float(__float_as_uint(x) ^ (c & zero));
}
struct CS { float2 a, b; };
template <int S, int B>
__device__ __forceinline__ CS qkv_cs(uint32_t cs_addr) {
  constexpr int COL = (B < 4) ? 64 * S + 16 * B : 192 + 16 * S;
  CS c; c.a = lds64f(cs_addr + COL * 4); c.b = lds64f(cs_addr + (COL + 8) * 4);
  return c;
}
template <int S, int B>
__device__ __forceinline__ void qkv_piece(const float (&am)[96], const float (&ar)[24], float2 s1, float2 s2, const CS c,
                                          uint2& w1, uint2& w2) {
  float a[8];
#pragma unroll
  for (int i = 0; i < 8; i++) a[i] = (B < 4) ? am[(B < 4 ? 32 * S + 8 * B : 0) + i] : ar[(B < 4 ? 0 : 8 * S) + i];
  w1.x = pack_bf16(s1.x * fmaf(s1.y, c.a.x, a[0]), s1.x * fmaf(s1.y, c.a.y, a[1]));
  w2.x = pack_bf16(s2.x * fmaf(s2.y, c.a.x, a[2]), s2.x * fmaf(s2.y, c.a.y, a[3]));
  w1.y = pack_bf16(s1.x * fmaf(s1.y, c.b.x, a[4]), s1.x * fmaf(s1.y, c.b.y, a[5]));
  w2.y = pack_bf16(s2.x * fmaf(s2.y, c.b.x, a[6]), s2.x * fmaf(s2.y, c.b.y, a[7]));
}
template <int B>
__device__ __forceinline__ void q_piece(const float (&am)[96], const float (&ar)[24], float m1, float m2, const CS c, uint2& w1, uint2& w2) {
  float a[8];
#pragma unroll
  for (int i = 0; i < 8; i++) a[i] = (B < 4) ? am[(B < 4 ? 8 * B : 0) + i] : ar[i];
  w1.x = pack_bf16(fmaf(m1, c.a.x, a[0]), fmaf(m1, c.a.y, a[1]));
  w2.x = pack_bf16(fmaf(m2, c.a.x, a[2]), fmaf(m2, c.a.y, a[3]));
  w1.y = pack_bf16(fmaf(m1, c.b.x, a[4]), fmaf(m1, c.b.y, a[5]));
  w2.y = pack_bf16(fmaf(m2, c.b.x, a[6]), fmaf(m2, c.b.y, a[7]));
}
__device__ __forceinline__ float tanhf_hw(float x) { float y; asm("tanh.approx.f32 %0, %1;" : "=f"(y) : "f"(x)); return y; }
__device__ __forceinline__ float swiglu(float ag, float au, float cg, float cu, const float3 s) {
  const float g = fmaf(s.y, cg, ag), u = fmaf(s.y, cu, au);
  const float t = tanhf_hw(g * s.x);
  return (g * u) * fmaf(t, s.z, s.z);
}
template <int NB>
__device__ __forceinline__ CS gu_cs(uint32_t cs_addr) {
  CS c; c.a = lds64f(cs_addr + (8 * NB) * 4); c.b = lds64f(cs_addr + (64 + 8 * NB) * 4);
  return c;
}
template <int NB>
__device__ __forceinline__ void gu_piece(const float (&acc)[64], const float3 s1, const float3 s2, const CS c, uint32_t (&h)[16]) {
  h[4 * (NB >> 1) + 2 * (NB & 1) + 0] = pack_bf16(swiglu(acc[4 * NB + 0], acc[32 + 4 * NB + 0], c.a.x, c.b.x, s1),
                                                  swiglu(acc[4 * NB + 1], acc[32 + 4 * NB + 1], c.a.y, c.b.y, s1));
  h[4 * (NB >> 1) + 2 * (NB & 1) + 1] = pack_bf16(swiglu(acc[4 * NB + 2], acc[32 + 4 * NB + 2], c.a.x, c.b.x, s2),
                                                  swiglu(acc[4 * NB + 3], acc[32 + 4 * NB + 3], c.a.y, c.b.y, s2));
}

struct AttnOps { uint2 q1[5], q2[5], k[3][5], v[3][5]; };
template <int H>
__device__ __forceinline__ void attn_qk(const AttnOps& o, const uint2 (&k)[5], uint32_t mlo, float ci, float (&s)[4]) {
  const uint32_t m = (H & 1) ? ~mlo : mlo;
  if (H == 0) { mma16816_c(s, o.q1[0].x, o.q2[0].x, o.q1[0].y, o.q2[0].y, k[0].x, k[0].y, ci); mma1688(s, o.q1[1].x & m, o.q2[1].x & m, k[1].x); }
  if (H == 1) { mma16816_c(s, o.q1[1].y, o.q2[1].y, o.q1[2].x, o.q2[2].x, k[1].y, k[2].x, ci); mma1688(s, o.q1[1].x & m, o.q2[1].x & m, k[1].x); }
  if (H == 2) { mma16816_c(s, o.q1[2].y, o.q2[2].y, o.q1[3].x, o.q2[3].x, k[2].y, k[3].x, ci); mma1688(s, o.q1[3].y & m, o.q2[3].y & m, k[3].y); }
  if (H == 3) { mma16816_c(s, o.q1[4].x, o.q2[4].x, o.q1[4].y, o.q2[4].y, k[4].x, k[4].y, ci); mma1688(s, o.q1[3].y & m, o.q2[3].y & m, k[3].y); }
}
template <int H>
__device__ __forceinline__ float4 attn_own(const AttnOps& o, uint32_t mlo, bool p0, bool p1) {
  float s1[4], s2[4];
  attn_qk<H>(o, o.k[1], mlo, 0.f, s1);
  attn_qk<H>(o, o.k[2], mlo, 0.f, s2);
  return make_float4(s1[0], s1[1], p0 ? s1[2] : s2[2], p1 ? s1[3] : s2[3]);
}
template <int H>
__device__ __forceinline__ void attn_softmax(const AttnOps& o, const float4 sc, uint32_t mlo, bool p0, bool p1, float bias, float c1, float c2,
                                             uint32_t pm, uint32_t (&P)[4]) {
  float s0[4];
  attn_qk<H>(o, o.k[0], mlo, bias, s0);
  const float a0 = p0 ? s0[0] : sc.x, a1 = p1 ? s0[1] : sc.y;
  const float b0 = sc.z, b1 = sc.w;
  float m1 = fmaxf(a0, a1), m2 = fmaxf(b0, b1);
  m1 = fmaxf(m1, __shfl_xor_sync(0xffffffffu, m1, 1)); m2 = fmaxf(m2, __shfl_xor_sync(0xffffffffu, m2, 1));
  m1 = fmaxf(m1, __shfl_xor_sync(0xffffffffu, m1, 2)); m2 = fmaxf(m2, __shfl_xor_sync(0xffffffffu, m2, 2));
  const float o1 = -m1 * c1, o2 = -m2 * c2;
  const float e0 = ex2f(fmaf(a0, c1, o1)), e1 = ex2f(fmaf(a1, c1, o1));
  const float f0 = ex2f(fmaf(b0, c2, o2)), f1 = ex2f(fmaf(b1, c2, o2));
  float l1 = e0 + e1, l2 = f0 + f1;
  l1 += __shfl_xor_sync(0xffffffffu, l1, 1); l2 += __shfl_xor_sync(0xffffffffu, l2, 1);
  l1 += __shfl_xor_sync(0xffffffffu, l1, 2); l2 += __shfl_xor_sync(0xffffffffu, l2, 2);
  const float i1 = rcpf(l1), i2 = rcpf(l2);
  const uint32_t w1 = pack_bf16(e0 * i1, e1 * i1), w2 = pack_bf16(f0 * i2, f1 * i2);
  P[0] = w1 & pm;  P[1] = w1 & ~pm;
  P[2] = w2 & pm;  P[3] = w2 & ~pm;
}
__device__ __forceinline__ void attn_pv(const uint32_t (&P)[4], uint32_t v0, uint32_t v1, uint32_t v2, uint32_t& w1, uint32_t& w2) {
  float o[4];
  mma16816_c(o, P[1], P[2], 0u, P[3], v1, v2, 0.f);
  mma1688(o, P[0], 0u, v0);
  w1 = pack_bf16(o[0], o[1]);
  w2 = pack_bf16(o[2], o[3]);
}
__device__ __forceinline__ void attn_compute(const AttnOps& o, const float4 (&sc)[4], bool first, int g, int t, float r1, float r2,
                                             uint32_t (&of)[20]) {
  const bool lo = t < 2;
  const uint32_t mlo = lo ? 0xffffffffu : 0u;
  const bool p0 = 2 * t > g, p1 = 2 * t + 1 > g;
  const uint32_t pm = (p0 ? 0x0000ffffu : 0u) | (p1 ? 0xffff0000u : 0u);
  const float bias = first ? -INFINITY : 0.f;
  const float cexp = 0.22360679774997896f * 1.4426950408889634f;
  const float c1 = cexp * r1, c2 = cexp * r2;
  uint32_t P0[4], P1[4], P2[4], P3[4];
  attn_softmax<0>(o, sc[0], mlo, p0, p1, bias, c1, c2, pm, P0);
  attn_softmax<1>(o, sc[1], mlo, p0, p1, bias, c1, c2, pm, P1);
  attn_softmax<2>(o, sc[2], mlo, p0, p1, bias, c1, c2, pm, P2);
  attn_softmax<3>(o, sc[3], mlo, p0, p1, bias, c1, c2, pm, P3);
  uint32_t c1_, c2_;
  attn_pv(P0, o.v[0][0].x, o.v[1][0].x, o.v[2][0].x, of[0], of[1]);
  attn_pv(P0, o.v[0][0].y, o.v[1][0].y, o.v[2][0].y, of[2], of[3]);
  attn_pv(P0, o.v[0][1].x, o.v[1][1].x, o.v[2][1].x, of[4], of[5]);
  attn_pv(P1, o.v[0][1].x, o.v[1][1].x, o.v[2][1].x, c1_, c2_);
  of[4] = lo ? of[4] : c1_; of[5] = lo ? of[5] : c2_;
  attn_pv(P1, o.v[0][1].y, o.v[1][1].y, o.v[2][1].y, of[6], of[7]);
  attn_pv(P1, o.v[0][2].x, o.v[1][2].x, o.v[2][2].x, of[8], of[9]);
  attn_pv(P2, o.v[0][2].y, o.v[1][2].y, o.v[2][2].y, of[10], of[11]);
  attn_pv(P2, o.v[0][3].x, o.v[1][3].x, o.v[2][3].x, of[12], of[13]);
  attn_pv(P2, o.v[0][3].y, o.v[1][3].y, o.v[2][3].y, of[14], of[15]);
  attn_pv(P3, o.v[0][3].y, o.v[1][3].y, o.v[2][3].y, c1_, c2_);
  of[14] = lo ? of[14] : c1_; of[15] = lo ? of[15] : c2_;
  attn_pv(P3, o.v[0][4].x, o.v[1][4].x, o.v[2][4].x, of[16], of[17]);
  attn_pv(P3, o.v[0][4].y, o.v[1][4].y, o.v[2][4].y, of[18], of[19]);
}
__device__ __forceinline__ void halo_load(uint64_t (&hv)[10], const uint4* src) {
#pragma unroll
  for (int b = 0; b < 5; b++)
    asm volatile("{\n.reg .b128 r;\nld.relaxed.gpu.global.b128 r, [%2];\nmov.b128 {%0, %1}, r;\n}"
                 : "=l"(hv[2 * b]), "=l"(hv[2 * b + 1]) : "l"(src + 32 * b) : "memory");
}
__device__ __forceinline__ void halo_reload(uint64_t (&hv)[10], const uint4* src) {
#pragma unroll
  for (int b = 0; b < 5; b++)
    asm volatile("{\n.reg .b128 r;\nld.relaxed.gpu.global.b128 r, [%2];\nmov.b128 {%0, %1}, r;\n}"
                 : "+l"(hv[2 * b]), "+l"(hv[2 * b + 1]) : "l"(src + 32 * b) : "memory");
}
__device__ __forceinline__ uint32_t halo_bad(const uint64_t (&hv)[10], uint32_t t) {
  uint32_t a[5];
#pragma unroll
  for (int i = 0; i < 5; i++)
    asm("lop3.b32 %0, %1, %2, %3, 0x7e;" : "=r"(a[i]) : "r"((uint32_t)hv[2 * i]), "r"((uint32_t)hv[2 * i + 1]), "r"(t));
  return a[0] | a[1] | a[2] | a[3] | a[4];
}

__device__ __forceinline__ void stat8(const uint4 v, float c, float& s, float& q) {
  float d;
  d = bf_lo(v.x) - c; s += d; q = fmaf(d, d, q);  d = bf_hi(v.x) - c; s += d; q = fmaf(d, d, q);
  d = bf_lo(v.y) - c; s += d; q = fmaf(d, d, q);  d = bf_hi(v.y) - c; s += d; q = fmaf(d, d, q);
  d = bf_lo(v.z) - c; s += d; q = fmaf(d, d, q);  d = bf_hi(v.z) - c; s += d; q = fmaf(d, d, q);
  d = bf_lo(v.w) - c; s += d; q = fmaf(d, d, q);  d = bf_hi(v.w) - c; s += d; q = fmaf(d, d, q);
}
__device__ __forceinline__ void add8(float* a, const uint4 v) {
  a[0] += bf_lo(v.x); a[1] += bf_hi(v.x); a[2] += bf_lo(v.y); a[3] += bf_hi(v.y);
  a[4] += bf_lo(v.z); a[5] += bf_hi(v.z); a[6] += bf_lo(v.w); a[7] += bf_hi(v.w);
}
__device__ __forceinline__ uint4 ldg128(const void* p) {
  uint4 v;
  asm volatile("ld.global.nc.L1::no_allocate.L2::128B.v4.u32 {%0, %1, %2, %3}, [%4];" : "=r"(v.x), "=r"(v.y), "=r"(v.z), "=r"(v.w) : "l"(p));
  return v;
}
__device__ __forceinline__ void col_task(float (&a)[16], const char* p, uint32_t step) {
#pragma unroll
  for (int i = 0; i < 8; i++) a[i] = 0.f;
  uint4 va[4], vb[4];
#pragma unroll
  for (int i = 0; i < 4; i++) { va[i] = ldg128(p); p += step; }
#pragma unroll 1
  for (int b = 0; b < 2; b++) {
#pragma unroll
    for (int i = 0; i < 4; i++) { vb[i] = ldg128(p); p += step; }
#pragma unroll
    for (int i = 0; i < 4; i++) add8(a, va[i]);
#pragma unroll
    for (int i = 0; i < 4; i++) { va[i] = ldg128(p); p += step; }
#pragma unroll
    for (int i = 0; i < 4; i++) add8(a, vb[i]);
  }
#pragma unroll
  for (int i = 0; i < 4; i++) add8(a, va[i]);
}
__device__ __forceinline__ uint32_t tagbad4(const uint4 u, uint32_t tag) { return (u.x ^ tag) | (u.y ^ tag) | (u.z ^ tag) | (u.w ^ tag); }
__device__ __forceinline__ uint4 fadd4(const uint4 a, const uint4 b) {
  return make_uint4(__float_as_uint(__uint_as_float(a.x) + __uint_as_float(b.x)), __float_as_uint(__uint_as_float(a.y) + __uint_as_float(b.y)),
                    __float_as_uint(__uint_as_float(a.z) + __uint_as_float(b.z)), __float_as_uint(__uint_as_float(a.w) + __uint_as_float(b.w)));
}
template <int N, int O>
__device__ __forceinline__ void treduce(float (&a)[16], int lane) {
  const bool up = lane & O;
#pragma unroll
  for (int i = 0; i < N / 2; i++) {
    const float keep = up ? a[N / 2 + i] : a[i], send = up ? a[i] : a[N / 2 + i];
    a[i] = keep + __shfl_xor_sync(0xffffffffu, send, O);
  }
}
__device__ __forceinline__ int col_of_lane(int lane) { return 8 * (lane & 1) + ((lane >> 4) & 1) * 4 + ((lane >> 3) & 1) * 2 + ((lane >> 2) & 1); }

template <bool INIT>
__device__ __forceinline__ void g2_h(float (&acc)[32], const uint32_t (&h)[16], uint32_t blo) {
  if (INIT) wgmma_rs64_init(acc, h[0], h[1], h[2], h[3], blo);
  else      wgmma_rs64(acc, h[0], h[1], h[2], h[3], blo);
  wgmma_rs64(acc, h[4], h[5], h[6], h[7], blo + 128);
  wgmma_rs64(acc, h[8], h[9], h[10], h[11], blo + 256);
  wgmma_rs64(acc, h[12], h[13], h[14], h[15], blo + 384);
}
__device__ __forceinline__ void g2_o(float (&acc)[32], const uint32_t (&o)[20], uint32_t blo) {
#pragma unroll
  for (int s = 0; s < 5; s++) wgmma_rs64(acc, o[4 * s], o[4 * s + 1], o[4 * s + 2], o[4 * s + 3], blo + 1536 + 128 * s);
}
__device__ __forceinline__ uint4 pack8(const float (&acc)[32], int v) {
  return make_uint4(pack_bf16(acc[8 * v + 0], acc[8 * v + 1]), pack_bf16(acc[8 * v + 2], acc[8 * v + 3]),
                    pack_bf16(acc[8 * v + 4], acc[8 * v + 5]), pack_bf16(acc[8 * v + 6], acc[8 * v + 7]));
}
__device__ __forceinline__ uint32_t add_bf16x2(uint32_t a, uint32_t b) {
  uint32_t r;
  asm("add.rn.bf16x2 %0, %1, %2;" : "=r"(r) : "r"(a), "r"(b));
  return r;
}
__device__ __forceinline__ void ldsm4(uint32_t* r, uint32_t a) {
  asm volatile("ldmatrix.sync.aligned.m8n8.x4.shared.b16 {%0, %1, %2, %3}, [%4];" : "=r"(r[0]), "=r"(r[1]), "=r"(r[2]), "=r"(r[3]) : "r"(a) : "memory");
}
__device__ __forceinline__ void store_tile(const uint4 (&f)[4], uint32_t ta, uint32_t tx) {
#pragma unroll
  for (int v = 0; v < 4; v++) stsm4(ta + (((2 * v) ^ tx) << 4), f[v]);
}

__global__ void __launch_bounds__(NTHREADS, 1)
fused_kernel(const __grid_constant__ CUtensorMap tmX, const __grid_constant__ CUtensorMap tmQA,
             const __grid_constant__ CUtensorMap tmQB, const __grid_constant__ CUtensorMap tmW1,
             const __grid_constant__ CUtensorMap tmW3, const __grid_constant__ CUtensorMap tmW2,
             const __grid_constant__ CUtensorMap tmWo, const __grid_constant__ CUtensorMap tmOut, const Params prm) {
  extern __shared__ __align__(1024) uint8_t smem_raw[];
  const uint32_t sb = smem_u32(smem_raw);
  const uint32_t bar0 = sb + SM_BAR;
  const int tid = threadIdx.x;
  const int warp = __shfl_sync(0xffffffffu, tid >> 5, 0);
  const int lane = tid & 31;
  const int j = blockIdx.x & 7, mt = blockIdx.x >> 3;
#define BAR(i) (bar0 + 8 * (i))

  if (warp < 4) {
    asm volatile("setmaxnreg.dec.sync.aligned.u32 56;");
    if (warp == 0) {
      if (elect_one()) {
        prefetch_tmap(&tmX); prefetch_tmap(&tmQA); prefetch_tmap(&tmQB);
#pragma unroll
        for (int i = 0; i < 3; i++) mbar_init(BAR(B_XFULL + i), 1);
#pragma unroll
        for (int i = 0; i < 4; i++) mbar_init(BAR(B_FULL + i), 1);
        asm volatile("fence.mbarrier_init.release.cluster;" ::: "memory");
#pragma unroll
        for (int ks = 0; ks < 4; ks++) {
          if ((ks & 1) == 0) {
            mbar_expect_tx(BAR(B_XFULL + (ks >> 1)), SLOT);
            tma3d(sb + SM_X + (ks >> 1) * SLOT, &tmX, 32 * ks, 64 * mt, 0, BAR(B_XFULL + (ks >> 1)));
            tma3d(sb + SM_X + (ks >> 1) * SLOT + 8192, &tmX, 32 * ks, 64 * mt, 1, BAR(B_XFULL + (ks >> 1)));
          }
          mbar_expect_tx(BAR(B_FULL + ks), QBYTES);
          tma3d(sb + SM_RING + ks * SLOT, &tmQA, 80 * j, 32 * ks, 0, BAR(B_FULL + ks));
          tma3d(sb + SM_RING + ks * SLOT + 12288, &tmQB, 80 * j + 64, 32 * ks, 0, BAR(B_FULL + ks));
        }
        mbar_expect_tx(BAR(B_XFULL + 2), SLOT);
        tma3d(sb + SM_X + 2 * SLOT, &tmX, 128, 64 * mt, 0, BAR(B_XFULL + 2));
        tma3d(sb + SM_X + 2 * SLOT + 8192, &tmX, 128, 64 * mt, 1, BAR(B_XFULL + 2));
        TSTAMP(5);
      }
      __syncwarp();
    } else if (warp == 1) {
      const int r = 128 * mt + 16 * j + (lane & 15);
      const __nv_bfloat16* p = prm.x + (size_t)r * D_ + 64 * (lane >> 4);
      asm volatile("prefetch.global.L2 [%0];" ::"l"(p));
    } else if (warp == 2) {
      const int r = 4 * mt + (lane >> 3), u = lane & 7;
      const __nv_bfloat16* p = prm.wqkv + (size_t)r * NQKV + 640 * (u >> 1) + 80 * j + 64 * (u & 1);
      if (u < 6) asm volatile("prefetch.global.L2 [%0];" ::"l"(p));
    } else
    if (warp == 3) {
      if (elect_one()) {
#pragma unroll
        for (int i = 3; i < B_COUNT; i++) {
          if (i >= B_FULL && i < B_EMPTY) continue;
          const uint32_t cnt = (i >= B_EMPTY && i < B_CFULL) ? 2u : (i >= B_CEMPTY && i < B_EPI) ? 2u : (i == B_REMPTY) ? 2u
                             : (i == B_CSFREE) ? 8u : (i >= B_EMPTYQ && i < B_XFREE) ? 3u : (i > B_INIT && i < B_EMPTYQ) ? 4u : 1u;
          mbar_init(BAR(i), cnt);
        }
#pragma unroll
        for (int i = 0; i < 9; i++) mbar_expect_tx(BAR(B_RFULL + i), 8192);
        asm volatile("fence.mbarrier_init.release.cluster;" ::: "memory");
      }
      __syncwarp();
    }
    asm volatile("bar.sync 0, 384;" ::: "memory");
    asm volatile("barrier.cluster.arrive.relaxed.aligned;" ::: "memory");
    const uint32_t ring = sb + SM_RING;
    if (warp == 0) {
      asm volatile("barrier.cluster.wait.acquire.aligned;" ::: "memory");
      if (elect_one()) {
        prefetch_tmap(&tmW1); prefetch_tmap(&tmW3); prefetch_tmap(&tmW2); prefetch_tmap(&tmWo); prefetch_tmap(&tmOut);
#pragma unroll 1
        for (int ks = 4; ks < 20; ks++) {
          if ((ks & 1) == 0 && ks < 18) {
            const int c = (ks >> 1) + 1;
            mbar_expect_tx(BAR(B_XFULL + c), SLOT);
            tma3d_mc(sb + SM_X + c * SLOT + (j & 1) * 8192, &tmX, 64 * c, 64 * mt, j & 1, BAR(B_XFULL + c));
          }
          const int s = ks & 3;
          mbar_wait(BAR(B_EMPTYQ + s), ((ks >> 2) & 1) ^ 1);
          mbar_expect_tx(BAR(B_FULL + s), QBYTES);
          tma3d(ring + s * SLOT, &tmQA, 80 * j, 32 * ks, 0, BAR(B_FULL + s));
          tma3d(ring + s * SLOT + 12288, &tmQB, 80 * j + 64, 32 * ks, 0, BAR(B_FULL + s));
        }
        TSTAMP(1);
#pragma unroll 1
        for (int g = 20; g < 50; g++) {
          const int s = g & 3, i = (g - 20) / 10, ks = (g - 20) - 10 * i;
          if (g < 44) mbar_wait(BAR(B_EMPTYQ + s), ((g >> 2) & 1) ^ 1);
          else        mbar_wait(BAR(B_EMPTY + s), (g >> 2) == 12);
          mbar_expect_tx(BAR(B_FULL + s), SLOT);
          tma2d(ring + s * SLOT, &tmW1, 192 * j + 64 * i, 64 * ks, BAR(B_FULL + s));
          tma2d(ring + s * SLOT + 8192, &tmW3, 192 * j + 64 * i, 64 * ks, BAR(B_FULL + s));
          if (g == W0_AT) {
            mbar_wait(BAR(B_XFREE), 0);
            mbar_expect_tx(BAR(B_CFULL), CSLOT);
            tma2d(sb + 24576, &tmWo, 0, 80 * j, BAR(B_CFULL));
          }
          if (g > W0_AT) tma2d(sb + 8192 * (g - W0_AT - 1), &tmW2, 0, 192 * j + 64 * (g - W0_AT - 1), BAR(B_CFULL));
        }
        TSTAMP(2);
#pragma unroll
        for (int q = 49 - W0_AT; q < 3; q++) tma2d(sb + 8192 * q, &tmW2, 0, 192 * j + 64 * q, BAR(B_CFULL));
#pragma unroll 1
        for (int c = 1; c < 10; c++) {
          if (c == 2) mbar_wait(BAR(B_EMPTY + 2), 1);
          if (c == 3) mbar_wait(BAR(B_EMPTY + 0), 0);
          if (c == 4) mbar_wait(BAR(B_EMPTY + 1), 0);
          const int s = c < 5 ? c : c - 5;
          if (c >= 5) mbar_wait(BAR(B_CEMPTY + s), 0);
          const uint32_t dst = sb + s * CSLOT;
          mbar_expect_tx(BAR(B_CFULL + s), CSLOT);
#pragma unroll
          for (int q = 0; q < 3; q++) tma2d(dst + 8192 * q, &tmW2, 64 * c, 192 * j + 64 * q, BAR(B_CFULL + s));
          tma2d(dst + 24576, &tmWo, 64 * c, 80 * j, BAR(B_CFULL + s));
        }
        TSTAMP(3);
      }
    } else {
      uint32_t tag = 0;
      if (warp != 2) tag = launch_tag();
      if (warp == 3) {
        if (lane == 0) { asm volatile("st.shared.b32 [%0], %1;" ::"r"(sb + SM_TAG), "r"(tag) : "memory"); mbar_arrive(BAR(B_TAG)); }
        float* const gd = g_cs + j * 4 * 512;
        if (lane < 16 && mt < 15) st_tagged32(gd + 16 * mt + lane, tag ^ 1u);
        if (lane < 16) st_tagged32(gd + 512 * (1 + (lane >> 3)) + 8 * mt + (lane & 7), tag ^ 1u);
      }
      if (warp == 1) {
        const int par = lane >> 4, hf = (lane >> 3) & 1, il = lane & 7;
        const uint32_t a0 = sb + SM_X + par * 8192 + (8 * j + il) * 128;
        if (hf == 0) st_tagged64(&g_stats[128 * mt + 2 * (8 * j + il) + par], tag ^ 1u, 0u);
#pragma unroll
        for (int u = 0; u < 10; u++)
          st_tagged(g_halo + ((j * 2 + u / 5) * 64 + 4 * mt + 3) * 160 + 32 * (u % 5) + lane, make_uint4(tag ^ 1u, 0u, tag ^ 1u, 0u));
        if (lane == 0) TSTAMP(15);
        mbar_wait(BAR(B_XFULL), 0);
        if (lane == 0) TSTAMP(7);
        const float c = bf_lo(lds32(a0 + il * 16));
        float s0 = 0.f, q0 = 0.f, s1 = 0.f, q1 = 0.f;
#pragma unroll 1
        for (int ch = 0; ch < 10; ch++) {
          mbar_wait(BAR(B_XFULL + ch), 0);
          const uint32_t a = a0 + ch * SLOT;
          const uint4 v0 = lds128(a + (((4 * hf + 0) ^ il) << 4)), v1 = lds128(a + (((4 * hf + 1) ^ il) << 4));
          const uint4 v2 = lds128(a + (((4 * hf + 2) ^ il) << 4)), v3 = lds128(a + (((4 * hf + 3) ^ il) << 4));
          stat8(v0, c, s0, q0); stat8(v1, c, s1, q1); stat8(v2, c, s0, q0); stat8(v3, c, s1, q1);
        }
        s0 += s1; q0 += q1;
        s0 += __shfl_xor_sync(0xffffffffu, s0, 8); q0 += __shfl_xor_sync(0xffffffffu, q0, 8);
        const float m = s0 * (1.0f / D_);
        const float var = fmaxf(fmaf(-m, m, q0 * (1.0f / D_)), 0.f);
        const float r = rsqrtf(var + 1e-5f);
        if (hf == 0) st_tagged64(&g_stats[128 * mt + 2 * (8 * j + il) + par], set_tag(__float_as_uint(r), tag), __float_as_uint(-(c + m)));
        __syncwarp();
        if (lane == 0) { mbar_arrive(BAR(B_PUB)); TSTAMP(8); }
      }
      float* const gdst = g_cs + j * 4 * 512;
      if (warp == 2) {
        int g = 0;
#pragma unroll 1
        for (int rnd = 0; rnd < 3; rnd++) {
          uint32_t off, step;
          if (rnd == 0) {
            const int blk = min(mt, 14), cq = lane & 3, rq = lane >> 2;
            if (blk < 12) {
              const int r = 2 * (rq & 3) + (rq >> 2);
              off = (blk >> 2) * 4096 + r * 128 + (((2 * (blk & 3) + (cq >> 1)) ^ r) << 4) + (cq & 1) * 8;
              step = 1024;
            } else {
              off = 12288 + (blk - 12) * 1024 + rq * 32 + (((cq >> 1) ^ (rq >> 2)) << 4) + (cq & 1) * 8;
              step = 256;
            }
          } else {
            const int r = (lane >> 1) & 7, hi = lane >> 4;
            off = (mt >> 3) * 8192 + (r + 8 * hi) * 128 + (((mt & 7) ^ r) << 4) + (lane & 1) * 8;
            step = 2048;
          }
          float a0 = 0.f, a1 = 0.f, a2 = 0.f, a3 = 0.f;
          const int gend = 20 + 10 * rnd;
#pragma unroll 1
          for (; g < gend; g++) {
            const int s = g & 3;
            mbar_wait(BAR(B_FULL + s), (g >> 2) & 1);
            const uint32_t p = ring + s * SLOT + off;
            uint2 v[4];
#pragma unroll
            for (int i = 0; i < 4; i++) v[i] = lds64u(p + i * step);
            __syncwarp();
            if (lane == 0) mbar_arrive(BAR(B_EMPTYQ + s));
            if (g == 8) { mbar_wait(BAR(B_TAG), 0); tag = lds32(sb + SM_TAG); }
#pragma unroll
            for (int i = 0; i < 4; i++) { a0 += bf_lo(v[i].x); a1 += bf_hi(v[i].x); a2 += bf_lo(v[i].y); a3 += bf_hi(v[i].y); }
          }
          const bool u4 = lane & 16, u3 = lane & 8;
          const float b0 = (u4 ? a2 : a0) + __shfl_xor_sync(0xffffffffu, u4 ? a0 : a2, 16);
          const float b1 = (u4 ? a3 : a1) + __shfl_xor_sync(0xffffffffu, u4 ? a1 : a3, 16);
          float v = (u3 ? b1 : b0) + __shfl_xor_sync(0xffffffffu, u3 ? b0 : b1, 8);
          v += __shfl_xor_sync(0xffffffffu, v, 4);
          if (rnd > 0) v += __shfl_xor_sync(0xffffffffu, v, 2);
          const int cs_ = 2 * (lane >> 4) + ((lane >> 3) & 1);
          if (rnd == 0) { if (!(lane & 4) && mt < 15) st_tagged32(gdst + 16 * mt + 4 * (lane & 3) + cs_, set_tag(__float_as_uint(v), tag)); }
          else          { if (!(lane & 6)) st_tagged32(gdst + 512 * rnd + 8 * mt + 4 * (lane & 1) + cs_, set_tag(__float_as_uint(v), tag)); }
          __syncwarp();
          if (lane == 0) { mbar_arrive(BAR(rnd == 0 ? B_PUBQ : B_PUB + rnd)); TSTAMP(rnd == 0 ? 14 : 15 + rnd); }
        }
      }
      if (warp == 1) {
        const int gofs = 512 * 3 + 256 * (mt & 1) + 64 * (mt >> 3) + 16 * ((mt >> 1) & 3);
        if (!(lane & 2)) st_tagged32(gdst + gofs + col_of_lane(lane), tag ^ 1u);
        mbar_wait(BAR(B_CSFREE), 0);
        if (elect_one()) {
#pragma unroll 1
          for (int u = 0; u < (j < 2 ? 16 : 8); u++) {
            const int ch = j + (u & 8);
            tma_store3d(&tmOut, sb + SM_X + ch * SLOT + (u & 7) * 2048, 64 * ch, 64 * mt + 16 * (u & 3), (u >> 2) & 1);
          }
          bulk_commit();
          asm volatile("cp.async.bulk.wait_group 0;" ::: "memory");
          mbar_arrive(BAR(B_XFREE));
          fence_async();
          asm volatile("st.release.gpu.global.u32 [%0], %1;" ::"l"(&g_init[mt * 8 + j]), "r"(tag) : "memory");
          TSTAMP(13);
        }
        __syncwarp();
        const char* p = reinterpret_cast<const char*>(((mt >> 3) ? prm.w3 : prm.w1) + (size_t)(320 * (mt & 1) + (lane >> 1)) * F_ + 8 * (lane & 1) +
                                                      192 * j + 128 + 16 * ((mt >> 1) & 3));
        float a[16];
        col_task(a, p, 16 * F_ * 2);
        treduce<8, 16>(a, lane); treduce<4, 8>(a, lane); treduce<2, 4>(a, lane);
        const float v = a[0] + __shfl_xor_sync(0xffffffffu, a[0], 2);
        if (!(lane & 2)) st_tagged32(gdst + gofs + col_of_lane(lane), set_tag(__float_as_uint(v), tag));
        __syncwarp();
        if (lane == 0) { mbar_arrive(BAR(B_PUB + 3)); TSTAMP(18); }
      }
      if (warp == 3) {
        const uint4* cs = reinterpret_cast<const uint4*>(g_cs + j * 4 * 512);
        {
          mbar_wait(BAR(B_PUB), 0);
          const uint4* st = reinterpret_cast<const uint4*>(g_stats + 128 * mt);
          uint4 u0, u1;
          uint32_t it = 0;
#pragma unroll 1
          while (true) {
            u0 = ld_tagged(st + lane); u1 = ld_tagged(st + lane + 32);
            if (!__any_sync(0xffffffffu, ((u0.x ^ tag) | (u0.z ^ tag) | (u1.x ^ tag) | (u1.z ^ tag)) & 1u) || ++it > SPIN_LIMIT) break;
          }
          sts128(sb + SM_CSB + lane * 16, u0); sts128(sb + SM_CSB + (lane + 32) * 16, u1);
          const int l2 = min(lane + 32, 59);
          mbar_wait(BAR(B_PUBQ), 0);
          it = 0;
#pragma unroll 1
          while (true) {
            u0 = ld_tagged(cs + lane); u1 = ld_tagged(cs + l2);
            if (!__any_sync(0xffffffffu, (tagbad4(u0, tag) | tagbad4(u1, tag)) & 1u) || ++it > SPIN_LIMIT) break;
          }
          sts128(sb + SM_CSA + lane * 16, u0); sts128(sb + SM_CSA + l2 * 16, u1);
          __syncwarp();
          if (lane == 0) { mbar_arrive(BAR(B_EPI)); TSTAMP(9); }
        }
#pragma unroll 1
        for (int rnd = 1; rnd < 4; rnd++) {
          mbar_wait(BAR(B_PUB + rnd), 0);
          if (rnd == 2) mbar_wait(BAR(B_CSFREE), 0);
          uint4 u0, u1;
          uint32_t it = 0;
#pragma unroll 1
          while (true) {
            u0 = ld_tagged(cs + 128 * rnd + lane);
            u1 = u0;
            if (rnd == 3) u1 = ld_tagged(cs + 128 * rnd + 64 + lane);
            if (!__any_sync(0xffffffffu, (tagbad4(u0, tag) | tagbad4(u1, tag)) & 1u) || ++it > SPIN_LIMIT) break;
          }
          if (rnd == 3) u0 = fadd4(u0, u1);
          sts128(sb + (rnd == 1 ? SM_CSC : rnd == 2 ? SM_CSB : SM_CSA) + lane * 16, u0);
          __syncwarp();
          if (lane == 0) { mbar_arrive(BAR(B_GU + rnd - 1)); TSTAMP(19 + rnd - 1); }
        }
        {
          uint32_t it = 0;
#pragma unroll 1
          while (true) {
            unsigned v;
            asm volatile("ld.acquire.gpu.global.u32 %0, [%1];" : "=r"(v) : "l"(&g_init[mt * 8 + (lane & 7)]) : "memory");
            if (!__any_sync(0xffffffffu, (v ^ tag) & 1u) || ++it > SPIN_LIMIT) break;
          }
          __syncwarp();
          if (lane == 0) mbar_arrive(BAR(B_INIT));
        }
      }
    }
    __syncwarp();
    if (warp != 0) asm volatile("barrier.cluster.wait.acquire.aligned;" ::: "memory");
  } else {
    asm volatile("setmaxnreg.inc.sync.aligned.u32 224;");
    const int w = (warp >> 2) - 1;
    const int tau = tid & 127;
    const int g = lane >> 2, t = lane & 3;
    const int half0 = 64 * mt + 16 * (warp & 3);
    const bool elect = tau == 0;
    const uint32_t xlo = (((sb + SM_X + w * 8192) & 0x3FFFFu) >> 4) | (1u << 16);
    const uint32_t ringq = (((sb + SM_RING) & 0x3FFFFu) >> 4) | (256u << 16);
    const uint32_t ringr = (((sb + SM_RING + 12288) & 0x3FFFFu) >> 4) | (64u << 16);
    const uint32_t ringg = (((sb + SM_RING) & 0x3FFFFu) >> 4) | (512u << 16);

    if (elect && w == 0) TSTAMP(6);
    float accm[96], accr[24];
#pragma unroll
    for (int i = 0; i < 96; i++) accm[i] = 0.f;
#pragma unroll
    for (int i = 0; i < 24; i++) accr[i] = 0.f;
    fence_regs(accm); fence_regs(accr);
    asm volatile("bar.sync 0, 384;" ::: "memory");
    asm volatile("barrier.cluster.arrive.relaxed.aligned;" ::: "memory");
    {
      const int arow = 16 * (warp & 3) + (lane & 15);
      const uint32_t abase = sb + SM_X + w * 8192 + arow * 128, ax = (lane >> 4) ^ (arow & 7);
      uint32_t af[2][8];
#define Q_LDA(KS) { ldsm4(af[(KS) & 1], abase + ((KS) >> 1) * SLOT + ((ax ^ (4 * ((KS) & 1))) << 4));      \
                    ldsm4(af[(KS) & 1] + 4, abase + ((KS) >> 1) * SLOT + ((ax ^ (4 * ((KS) & 1) + 2)) << 4)); }
      mbar_wait(BAR(B_XFULL), 0);
      Q_LDA(0)
#pragma unroll 4
      for (int ks = 0; ks < 20; ks++) {
        const int s = ks & 3;
        mbar_wait(BAR(B_FULL + s), (ks >> 2) & 1);
        if (ks == 0 && elect && w == 0) TSTAMP(24);
        wg_fence();
        const uint32_t b = ringq + s * 1024, br = ringr + s * 1024;
        const uint32_t (&a)[8] = af[ks & 1];
        wgmma_rs48r(accr, a[0], a[1], a[2], a[3], br);
        wgmma_rs192(accm, a[0], a[1], a[2], a[3], b);
        wgmma_rs48r(accr, a[4], a[5], a[6], a[7], br + 32);
        wgmma_rs192(accm, a[4], a[5], a[6], a[7], b + 128);
        wg_commit();
        if (ks < 19 && (ks & 1)) mbar_wait(BAR(B_XFULL + ((ks + 1) >> 1)), 0);
        wg_wait<1>();
        if (ks > 0 && elect) mbar_arrive(BAR(B_EMPTYQ + ((ks - 1) & 3)));
        if (ks < 19) Q_LDA(ks + 1)
      }
    }
    if (elect && w == 0) TSTAMP(25);
    asm volatile("barrier.cluster.wait.acquire.aligned;" ::: "memory");

    float accA[64], accB[64];
    uint32_t h0[16], h1[16], h2[16], of[20];
    AttnOps ao;

    uint32_t zero;
    asm volatile("mov.b32 %0, 0;" : "=r"(zero));
#define GU_STAGE0(ACC, G, FIRST)                                                       \
    {                                                                                  \
      mbar_wait(BAR(B_FULL + ((G) & 3)), ((G) >> 2) & 1);                              \
      wg_fence();                                                                      \
      const uint32_t a = xlo + (((G) - 20) % 10) * 1024, b = ringg + ((G) & 3) * 1024; \
      if ((FIRST) == 1) wgmma_ss128_init(ACC, a, b);                                   \
      else if ((FIRST) == 2) wgmma_ss128_sc(ACC, a, b, zero);                          \
      else wgmma_ss128(ACC, a, b);                                                     \
      wgmma_ss128(ACC, a + 2, b + 128);                                                \
      wgmma_ss128(ACC, a + 4, b + 256);                                                \
      wgmma_ss128(ACC, a + 6, b + 384);                                                \
      wg_commit();                                                                     \
    }
#define GU_REL(G)                                                                      \
    {                                                                                  \
      wg_wait<1>();                                                                    \
      if (elect) mbar_arrive(BAR(((G) <= 40 ? B_EMPTYQ : B_EMPTY) + (((G) - 1) & 3))); \
      if (elect) TSTAMP(64 + 32 * w + (G) - 20);                                       \
    }
#define GU_STAGE(ACC, G, FIRST) GU_STAGE0(ACC, G, FIRST) GU_REL(G)
#define PIN2(A, B) { const uint32_t z_ = __float_as_uint(pin(0.f, prm.zero)); A = __uint_as_float(__float_as_uint(A) ^ z_); B = __uint_as_float(__float_as_uint(B) ^ z_); }

    GU_STAGE(accA, 20, 1)
    fence_regs(accm); fence_regs(accr);
    GU_STAGE(accA, 21, 0)
    GU_STAGE(accA, 22, 0)
    mbar_wait(BAR(B_EPI), 0);
    const uint32_t st_addr = sb + SM_CSB + (2 * (16 * (warp & 3) + g) + w) * 8;
    float2 s1 = lds64f(st_addr), s2 = lds64f(st_addr + 128);
    const uint32_t tag = __float_as_uint(s1.x) & 1u;
    const uint32_t csA = sb + SM_CSA + t * 8;
    uint4* halo = g_halo + ((j * 2 + w) * 64 + 4 * mt + (warp & 3)) * 160 + lane;
    CS ca, cb;
#define K_LOAD(R, B) R = qkv_cs<1, B>(csA);
#define V_LOAD(R, B) R = qkv_cs<2, B>(csA);
#define Q_LOAD(R, B) R = qkv_cs<0, B>(csA);
#define K_PIECE(R, B) qkv_piece<1, B>(accm, accr, s1, s2, R, ao.k[1][B], ao.k[2][B]);
#define V_PIECE(R, B) qkv_piece<2, B>(accm, accr, s1, s2, R, ao.v[1][B], ao.v[2][B]); ao.v[2][B].x = movm(ao.v[2][B].x); ao.v[2][B].y = movm(ao.v[2][B].y);
#define V_MOVM(B) ao.v[1][B].x = movm(ao.v[1][B].x); ao.v[1][B].y = movm(ao.v[1][B].y);
#define Q_PIECE(R, B) q_piece<B>(accm, accr, s1.y, s2.y, R, ao.q1[B], ao.q2[B]);
    K_LOAD(ca, 0)
    K_PIECE(ca, 0)
    ao.k[2][0].x = set_tag(ao.k[2][0].x, tag);
    V_LOAD(ca, 0) K_LOAD(cb, 1)
    GU_STAGE0(accA, 23, 0)
    PIN2(s1.y, s2.y) V_PIECE(ca, 0) K_PIECE(cb, 1)
    ao.k[2][1].x = set_tag(ao.k[2][1].x, tag); ao.k[2][1].y = set_tag(ao.k[2][1].y, tag);
    V_LOAD(ca, 1) K_LOAD(cb, 2)
    GU_REL(23)
    GU_STAGE0(accA, 24, 0)
    PIN2(s1.y, s2.y) V_PIECE(ca, 1) K_PIECE(cb, 2)
    ao.k[2][2].y = set_tag(ao.k[2][2].y, tag);
    st_tagged(halo, make_uint4(set_tag(ao.v[2][0].x, tag), ao.v[2][0].y, set_tag(ao.v[2][1].x, tag), ao.v[2][1].y));
    st_tagged(halo + 32, make_uint4(ao.k[2][0].x, ao.k[2][0].y, ao.k[2][1].y, ao.k[2][2].x));
    V_LOAD(ca, 2) K_LOAD(cb, 3)
    GU_REL(24)
    GU_STAGE0(accA, 25, 0)
    PIN2(s1.y, s2.y) V_PIECE(ca, 2) K_PIECE(cb, 3)
    V_LOAD(ca, 3) K_LOAD(cb, 4)
    GU_REL(25)
    GU_STAGE0(accA, 26, 0)
    PIN2(s1.y, s2.y) V_PIECE(ca, 3) K_PIECE(cb, 4)
    ao.k[2][4].x = set_tag(ao.k[2][4].x, tag);
    st_tagged(halo + 64, make_uint4(set_tag(ao.v[2][2].x, tag), ao.v[2][2].y, set_tag(ao.v[2][3].x, tag), ao.v[2][3].y));
    st_tagged(halo + 128, make_uint4(ao.k[2][2].y, ao.k[2][3].x, ao.k[2][4].x, ao.k[2][4].y));
    V_LOAD(ca, 4) Q_LOAD(cb, 0)
    GU_REL(26)
    GU_STAGE0(accA, 27, 0)
    PIN2(s1.y, s2.y) V_PIECE(ca, 4)
    st_tagged(halo + 96, make_uint4(ao.k[2][1].x, ao.k[2][3].y, set_tag(ao.v[2][4].x, tag), ao.v[2][4].y));
    Q_PIECE(cb, 0)
    Q_LOAD(ca, 1) Q_LOAD(cb, 2)
    GU_REL(27)
    GU_STAGE0(accA, 28, 0)
    PIN2(s1.y, s2.y) Q_PIECE(ca, 1) Q_PIECE(cb, 2) V_MOVM(0) V_MOVM(1)
    Q_LOAD(ca, 3) Q_LOAD(cb, 4)
    const bool first = half0 == 0;
    const uint4* const hsrc = (first ? halo : halo - 160) + (ao.q2[2].y & prm.zero);
    uint64_t hv[10];
    halo_load(hv, hsrc);
    GU_REL(28)
    GU_STAGE0(accA, 29, 0)
    PIN2(s1.y, s2.y) Q_PIECE(ca, 3) Q_PIECE(cb, 4) V_MOVM(2) V_MOVM(3) V_MOVM(4)
    GU_REL(29)
    __syncwarp();
    if (lane == 0) mbar_arrive(BAR(B_CSFREE));
    wg_wait<0>();
    fence_regs(accA);
    if (elect) mbar_arrive(BAR(B_EMPTYQ + 1));
    if (elect && w == 0) TSTAMP(26);
    mbar_wait(BAR(B_EPI), 0);
    {
      float4 sc[4];
      {
        const uint32_t mlo = t < 2 ? 0xffffffffu : 0u;
        const bool p0 = 2 * t > g, p1 = 2 * t + 1 > g;
        sc[0] = attn_own<0>(ao, mlo, p0, p1); sc[1] = attn_own<1>(ao, mlo, p0, p1);
        sc[2] = attn_own<2>(ao, mlo, p0, p1); sc[3] = attn_own<3>(ao, mlo, p0, p1);
      }
      const uint32_t tz = tag ^ __float_as_uint(pin(0.f, prm.zero)) ^ (__float_as_uint(sc[3].w) & prm.zero);
      uint32_t it = 0;
#pragma unroll 1
      while (__any_sync(0xffffffffu, halo_bad(hv, tz) & 1u) && ++it < SPIN_LIMIT) halo_reload(hv, hsrc);
#define HLO(i) ((uint32_t)hv[i])
#define HHI(i) ((uint32_t)(hv[i] >> 32))
      ao.v[0][0] = make_uint2(HLO(0), HHI(0)); ao.v[0][1] = make_uint2(HLO(1), HHI(1));
      ao.v[0][2] = make_uint2(HLO(4), HHI(4)); ao.v[0][3] = make_uint2(HLO(5), HHI(5));
      ao.v[0][4] = make_uint2(HLO(7), HHI(7));
      ao.k[0][0] = make_uint2(HLO(2), HHI(2)); ao.k[0][1] = make_uint2(HLO(6), HLO(3));
      ao.k[0][2] = make_uint2(HHI(3), HLO(8)); ao.k[0][3] = make_uint2(HHI(8), HHI(6));
      ao.k[0][4] = make_uint2(HLO(9), HHI(9));
      attn_compute(ao, sc, first, g, t, s1.x, s2.x, of);
    }
    if (elect && w == 0) TSTAMP(22);

    float3 e1 = make_float3(0.5f * s1.x, s1.y, 0.5f * s1.x * s1.x);
    float3 e2 = make_float3(0.5f * s2.x, s2.y, 0.5f * s2.x * s2.x);
    const uint32_t csC = sb + SM_CSC + t * 8, csB = sb + SM_CSB + t * 8;
    GU_STAGE0(accB, 30, 1)
    mbar_wait(BAR(B_GU + 0), 0);
#define GU_PIECE(ACC, N, CSADDR, H) PIN2(e1.y, e2.y) GU_PIECE0(ACC, N, CSADDR, H)
#define GU_PIECE0(ACC, N, CSADDR, H) gu_piece<N>(ACC, e1, e2, ca, H); if ((N) < 7) ca = gu_cs<((N) < 7 ? (N) + 1 : 7)>(CSADDR);
    ca = gu_cs<0>(csC);
    GU_PIECE(accA, 0, csC, h0)
    GU_STAGE(accB, 31, 0) GU_PIECE(accA, 1, csC, h0)
    GU_STAGE(accB, 32, 0) GU_PIECE(accA, 2, csC, h0)
    GU_STAGE(accB, 33, 0) GU_PIECE(accA, 3, csC, h0)
    GU_STAGE(accB, 34, 0) GU_PIECE(accA, 4, csC, h0)
    GU_STAGE(accB, 35, 0) GU_PIECE(accA, 5, csC, h0)
    GU_STAGE(accB, 36, 0) GU_PIECE(accA, 6, csC, h0)
    GU_STAGE(accB, 37, 0) GU_PIECE(accA, 7, csC, h0)
    GU_STAGE(accB, 38, 0)
    GU_STAGE(accB, 39, 0)
    if (elect && w == 0) TSTAMP(27);

    float (&accC)[64] = accA;
    GU_STAGE(accC, 40, 2)
    fence_regs(accB);
    GU_STAGE(accC, 41, 0)
    GU_STAGE(accC, 42, 0)
    mbar_wait(BAR(B_GU + 1), 0);
    ca = gu_cs<0>(csB);
    GU_PIECE(accB, 0, csB, h1)
    GU_STAGE(accC, 43, 0) GU_PIECE(accB, 1, csB, h1)
    GU_STAGE(accC, 44, 0) GU_PIECE(accB, 2, csB, h1)
    GU_STAGE(accC, 45, 0) GU_PIECE(accB, 3, csB, h1)
    GU_STAGE(accC, 46, 0) GU_PIECE(accB, 4, csB, h1)
    GU_STAGE(accC, 47, 0) GU_PIECE(accB, 5, csB, h1)
    const int rho = j & 1;
    const uint32_t peer_bar0 = mapa(bar0, rho ^ 1);
    GU_STAGE(accC, 48, 0)
    if (elect) mbar_arrive_remote(peer_bar0 + 8 * B_REMPTY);
    GU_PIECE(accB, 6, csB, h1)
    GU_STAGE(accC, 49, 0)
    GU_PIECE(accB, 7, csB, h1)
    if (elect && w == 0) TSTAMP(28);

    float acc0[32], acc1[32];
    const uint32_t cdesc = ((sb & 0x3FFFFu) >> 4) | (1u << 16);
    constexpr uint32_t CS16 = CSLOT >> 4;

    const uint32_t csA2 = sb + SM_CSA + t * 8;
    mbar_wait(BAR(B_CFULL + 0), 0);
    wg_fence();
    g2_h<true>(acc0, h0, cdesc);
    g2_h<false>(acc0, h1, cdesc + 512);
    wg_commit();
    wg_wait<1>();
    if (elect) mbar_arrive(BAR(B_EMPTY + 1));
    fence_regs(accC);
    mbar_wait(BAR(B_GU + 2), 0);
    ca = gu_cs<0>(csA2);
    GU_PIECE0(accC, 0, csA2, h2) GU_PIECE0(accC, 1, csA2, h2)
    wg_fence();
    g2_o(acc0, of, cdesc);
    wgmma_rs64(acc0, h2[0], h2[1], h2[2], h2[3], cdesc + 1024);
    wg_commit();
    GU_PIECE0(accC, 2, csA2, h2) GU_PIECE0(accC, 3, csA2, h2) GU_PIECE0(accC, 4, csA2, h2) GU_PIECE0(accC, 5, csA2, h2)
    wg_fence();
    wgmma_rs64(acc0, h2[4], h2[5], h2[6], h2[7], cdesc + 1024 + 128);
    wgmma_rs64(acc0, h2[8], h2[9], h2[10], h2[11], cdesc + 1024 + 256);
    wg_commit();
    GU_PIECE0(accC, 6, csA2, h2) GU_PIECE0(accC, 7, csA2, h2)
    wg_fence();
    wgmma_rs64(acc0, h2[12], h2[13], h2[14], h2[15], cdesc + 1024 + 384);
    wg_commit();
    if (elect && w == 0) TSTAMP(29);

    const bool keeper = (w == rho);
    const uint32_t wofs = (warp & 3) * 2048;
    const uint32_t rbuf = sb + SM_RECV + wofs;
    const uint32_t peer_buf = mapa(rbuf, rho ^ 1) + lane * 16;
    const int trow = (lane & 7) + (lane & 8);
    const uint32_t tofs = trow * 128, tx = (lane >> 4) ^ (trow & 7);
    uint4 kp[4];
#define RBUF(K) (rbuf + ((K) & 3) * 8192)
#define PACK(ACC) { kp[0] = pack8(ACC, 0); kp[1] = pack8(ACC, 1); kp[2] = pack8(ACC, 2); kp[3] = pack8(ACC, 3); }
#define KEEP_LOAD(K)                                                                             \
      {                                                                                          \
        _Pragma("unroll")                                                                        \
        for (int v = 0; v < 4; v++) ku[v] = lds128(RBUF(K) + v * 512 + lane * 16);               \
      }
#define KEEP_TILE(K)                                                                             \
      {                                                                                          \
        _Pragma("unroll")                                                                        \
        for (int v = 0; v < 4; v++)                                                              \
          kp[v] = make_uint4(add_bf16x2(kp[v].x, ku[v].x), add_bf16x2(kp[v].y, ku[v].y), add_bf16x2(kp[v].z, ku[v].z), add_bf16x2(kp[v].w, ku[v].w)); \
        __syncwarp();                                                                            \
        store_tile(kp, RBUF(K) + tofs, tx);                                                      \
      }
#define KEEP_OUT(K)                                                                              \
      {                                                                                          \
        fence_async_smem();                                                                      \
        __syncwarp();                                                                            \
        if (elect_one()) { tma_add3d(&tmOut, RBUF(K), 64 * (K), half0, w); bulk_commit(); }      \
      }
#define SEND(ACC, K)                                                                             \
      {                                                                                          \
        _Pragma("unroll")                                                                        \
        for (int v = 0; v < 4; v++) st_async(peer_buf + ((K) & 3) * 8192 + v * 512, pack8(ACC, v), peer_bar0 + 8 * (B_RFULL + (K))); \
      }
#define RLAG 2
#define G2_CHUNK(CUR, PREV, C)                                                                   \
      {                                                                                          \
        const int s_ = (C) < 5 ? (C) : (C) - 5;                                                  \
        const uint32_t bl = cdesc + s_ * CS16;                                                   \
        const bool okx = keeper ? ((C) < 2 || mbar_test(BAR(B_RFULL + (C) - 2), 0))              \
                                : (((C) - 1 < RLAG && (C) > 1) || mbar_test(BAR(B_REMPTY + (C) - 1), 0)); \
        const bool oki = (C) != 2 || !keeper || mbar_test(BAR(B_INIT), 0);                       \
        wg_fence();                                                                              \
        g2_h<true>(CUR, h0, bl);                                                                 \
        g2_h<false>(CUR, h1, bl + 512);                                                          \
        wg_commit();                                                                             \
        wg_wait<1>();                                                                            \
        if ((C) - 1 < 5 && elect) mbar_arrive(BAR(B_CEMPTY + (C) - 1));                          \
        fence_regs(PREV);                                                                        \
        if (keeper) {                                                                            \
          if ((C) >= 2) {                                                                        \
            uint4 ku[4];                                                                         \
            if (!okx) mbar_wait(BAR(B_RFULL + (C) - 2), 0);                                      \
            KEEP_LOAD((C) - 2)                                                                   \
              \
            if ((C) - 2 + RLAG < 9 && elect_one()) { bulk_wait_read<1>(); mbar_arrive_remote(peer_bar0 + 8 * (B_REMPTY + (C) - 2 + RLAG)); } \
            KEEP_TILE((C) - 2)                                                                   \
          }                                                                                      \
        } else {                                                                                 \
          if (!okx) mbar_wait(BAR(B_REMPTY + (C) - 1), 0);         \
          SEND(PREV, (C) - 1)                                                                    \
        }                                                                                        \
        wg_fence();                                                                              \
        g2_o(CUR, of, bl);                                                                       \
        g2_h<false>(CUR, h2, bl + 1024);                                                         \
        wg_commit();                                                                             \
        const int n_ = (C) + 1 < 5 ? (C) + 1 : (C) - 4;                                          \
        const bool okc = (C) == 9 || mbar_test(BAR(B_CFULL + n_), (C) + 1 < 5 ? 0 : 1);          \
        if (keeper) {                                                                            \
          if ((C) >= 2) {                                                                        \
            if (!oki) mbar_wait(BAR(B_INIT), 0);                    \
            KEEP_OUT((C) - 2)                                                                    \
          }                                                                                      \
          PACK(PREV)                                                                             \
        }                                                                                        \
        if (!okc) mbar_wait(BAR(B_CFULL + n_), (C) + 1 < 5 ? 0 : 1);                             \
      }                                                                                          \
      if (elect && w == 0) TSTAMP(32 + 3 * ((C) - 1));
    mbar_wait(BAR(B_CFULL + 1), 0);
    G2_CHUNK(acc1, acc0, 1) G2_CHUNK(acc0, acc1, 2) G2_CHUNK(acc1, acc0, 3) G2_CHUNK(acc0, acc1, 4)
    G2_CHUNK(acc1, acc0, 5) G2_CHUNK(acc0, acc1, 6) G2_CHUNK(acc1, acc0, 7) G2_CHUNK(acc0, acc1, 8)
    G2_CHUNK(acc1, acc0, 9)
    if (keeper) {
      uint4 ku[4];
      mbar_wait(BAR(B_RFULL + 8), 0);
      KEEP_LOAD(8)
      KEEP_TILE(8)
      KEEP_OUT(8)
    }
    wg_wait<0>();
    fence_regs(acc1);
    if (elect && w == 0) TSTAMP(30);
    {
      PACK(acc1)
      const uint32_t b_ = sb + SM_LAST + w * 8192 + wofs;
      store_tile(kp, b_ + tofs, tx);
      fence_async_smem();
      __syncwarp();
      if (elect_one()) { tma_add3d(&tmOut, b_, 64 * 9, half0, w); bulk_commit(); bulk_wait_read<0>(); }
      if (elect) { TSTAMP(31); GSTAMP(63); }
      if (elect && !keeper) atomicAdd(&g_done[0], 1u);
    }

  }
#undef BAR
}

typedef CUresult (*EncodeFn)(CUtensorMap*, CUtensorMapDataType, cuuint32_t, void*, const cuuint64_t*, const cuuint64_t*,
                             const cuuint32_t*, const cuuint32_t*, CUtensorMapInterleave, CUtensorMapSwizzle,
                             CUtensorMapL2promotion, CUtensorMapFloatOOBfill);

CUtensorMap make_map(EncodeFn enc, const void* base, int rank, const cuuint64_t* dims, const cuuint64_t* strides, const cuuint32_t* box,
                     CUtensorMapSwizzle sw = CU_TENSOR_MAP_SWIZZLE_128B) {
  CUtensorMap m;
  const cuuint32_t es[3] = {1, 1, 1};
  enc(&m, CU_TENSOR_MAP_DATA_TYPE_BFLOAT16, (cuuint32_t)rank, const_cast<void*>(base), dims, strides, box, es,
      CU_TENSOR_MAP_INTERLEAVE_NONE, sw, CU_TENSOR_MAP_L2_PROMOTION_L2_128B, CU_TENSOR_MAP_FLOAT_OOB_FILL_NONE);
  return m;
}

}

extern "C" void kernel_launch(void* const* d_in, const int* in_sizes, int n_in, void* d_out, int out_size) {
  (void)in_sizes; (void)n_in; (void)out_size;
  static EncodeFn enc = nullptr;
  if (!enc) {
    void* fn = nullptr;
    cudaDriverEntryPointQueryResult q;
    cudaGetDriverEntryPoint("cuTensorMapEncodeTiled", &fn, cudaEnableDefault, &q);
    enc = (EncodeFn)fn;
    cudaFuncSetAttribute(fused_kernel, cudaFuncAttributeMaxDynamicSharedMemorySize, SM_TOTAL);
  }
  Params p;
  p.x = (const __nv_bfloat16*)d_in[0];
  p.wqkv = (const __nv_bfloat16*)d_in[1];
  p.w1 = (const __nv_bfloat16*)d_in[4];
  p.w3 = (const __nv_bfloat16*)d_in[5];
  p.out = (__nv_bfloat16*)d_out;
  p.zero = 0;
  const void* wo = d_in[2];
  const void* w2 = d_in[6];

  CUtensorMap tmX, tmQA, tmQB, tmW1, tmW3, tmW2, tmWo, tmOut;
  { const cuuint64_t d[3] = {D_, S_ / 2, 2}, s[2] = {D_ * 4, D_ * 2}; const cuuint32_t b[3] = {64, 64, 1}; tmX = make_map(enc, p.x, 3, d, s, b); }
  { const cuuint64_t d[3] = {D_, S_ / 2, 2}, s[2] = {D_ * 4, D_ * 2}; const cuuint32_t b[3] = {64, 16, 1}; tmOut = make_map(enc, p.out, 3, d, s, b); }
  { const cuuint64_t d[3] = {D_, D_, 3}, s[2] = {NQKV * 2, D_ * 2};
    const cuuint32_t b[3] = {64, 32, 3}; tmQA = make_map(enc, p.wqkv, 3, d, s, b);
    const cuuint32_t b2[3] = {16, 32, 3}; tmQB = make_map(enc, p.wqkv, 3, d, s, b2, CU_TENSOR_MAP_SWIZZLE_32B); }
  { const cuuint64_t d[2] = {F_, D_}, s[1] = {F_ * 2}; const cuuint32_t b[2] = {64, 64}; tmW1 = make_map(enc, p.w1, 2, d, s, b); tmW3 = make_map(enc, p.w3, 2, d, s, b); }
  { const cuuint64_t d[2] = {D_, F_}, s[1] = {D_ * 2}; const cuuint32_t b[2] = {64, 64}; tmW2 = make_map(enc, w2, 2, d, s, b); }
  { const cuuint64_t d[2] = {D_, D_}, s[1] = {D_ * 2}; const cuuint32_t b[2] = {64, 80}; tmWo = make_map(enc, wo, 2, d, s, b); }

  cudaLaunchConfig_t cfg = {};
  cfg.gridDim = dim3(128);
  cfg.blockDim = dim3(NTHREADS);
  cfg.dynamicSmemBytes = SM_TOTAL;
  cfg.stream = cudaStreamPerThread;
  cudaLaunchAttribute at[1];
  at[0].id = cudaLaunchAttributeClusterDimension;
  at[0].val.clusterDim.x = 2; at[0].val.clusterDim.y = 1; at[0].val.clusterDim.z = 1;
  cfg.attrs = at; cfg.numAttrs = 1;
  cudaLaunchKernelEx(&cfg, fused_kernel, tmX, tmQA, tmQB, tmW1, tmW3, tmW2, tmWo, tmOut, p);
}
```
